```python
import torch

def _softmax(x, axis=-1):
    return torch.softmax(x, dim=axis)
def _gelu(x):
    return torch.nn.functional.gelu(x, approximate="tanh")
def _silu(x):
    return torch.nn.functional.silu(x)
def _sigmoid(x):
    return torch.sigmoid(x)
def _layernorm(x, axis=-1, eps=1e-5):
    m = x.mean(dim=axis, keepdim=True)
    v = x.var(dim=axis, keepdim=True, unbiased=False)
    return (x - m) / torch.sqrt(v + eps)
def _scatter_add(tgt, idx, src, axis=0):
    return tgt.clone().index_add_(axis, idx, src)
def _segment_sum(src, seg, n):
    out = torch.zeros((n,) + src.shape[1:], dtype=src.dtype)
    return out.index_add_(0, seg, src)
def _pad(x, pw):
    flat = tuple(v for pair in reversed(pw) for v in pair)
    return torch.nn.functional.pad(x, flat)

kernel_name = 'sequential_preLN__gqa_block_cached__dense_activation_squared_relu__decode'

def setup_inputs():

    _w = (lambda a: (lambda t: t.to(torch.bfloat16) if t.is_floating_point() else t)(torch.as_tensor(a)))
    def _A_setup():
        B, Sq, D = 2, 1, 512
        Hq, Hkv, Sk, Dh = 32, 32, 8192, 128
        assert Hq % Hkv == 0, (Hq, Hkv)
        return {
            "x": _w((lambda *s: torch.randn(*s, dtype=torch.bfloat16) * 0.05)(B, Sq, D)),
            "k_cache": _w((lambda *s: torch.randn(*s, dtype=torch.bfloat16) * 3.2)(B, Hkv, Sk, Dh)),
            "v_cache": _w((lambda *s: torch.randn(*s, dtype=torch.bfloat16) * 0.4)(B, Hkv, Sk, Dh)),
            "wq": _w((lambda *s: torch.randn(*s, dtype=torch.bfloat16) * 3.2)(D, Hq * Dh) * (D ** -0.5)),
            "wo": _w((lambda *s: torch.randn(*s, dtype=torch.bfloat16) * 0.4)(Hq * Dh, D) * ((Hq * Dh) ** -0.5)),
        }
    _A_in = _A_setup()

    def _B_setup():
        B, S, D, F = 2, 1, 512, 1376
        return {
            "x": _w((lambda *s: torch.randn(*s, dtype=torch.bfloat16) * 0.05)(B, S, D)),
            "w1": _w((lambda *s: torch.randn(*s, dtype=torch.bfloat16) * 0.05)(D, F)),
            "b1": _w((lambda *s: torch.randn(*s, dtype=torch.bfloat16) * 0.8)(F)),
            "w2": _w((lambda *s: torch.randn(*s, dtype=torch.bfloat16) * 0.05)(F, D)),
            "b2": _w((lambda *s: torch.randn(*s, dtype=torch.bfloat16) * 3.2)(D)),
        }
    _B_in = _B_setup()

    return {
        "A_x": _A_in["x"],
        "A_k_cache": _A_in["k_cache"],
        "A_v_cache": _A_in["v_cache"],
        "A_wq": _A_in["wq"],
        "A_wo": _A_in["wo"],
        "B_x": _B_in["x"],
        "B_w1": _B_in["w1"],
        "B_b1": _B_in["b1"],
        "B_w2": _B_in["w2"],
        "B_b2": _B_in["b2"],
    }

def reference(A_x, A_k_cache, A_v_cache, A_wq, A_wo, B_x, B_w1, B_b1, B_w2, B_b2):
    def _A_ref(x, k_cache, v_cache, wq, wo):
        B, Sq, D = x.shape
        Hq, Dh = 32, 128
        Hkv = k_cache.shape[1]
        rep = Hq // Hkv
        q = (lambda x, *d: x.permute(*d))((x @ wq).reshape(B, Sq, Hq, Dh), 0, 2, 1, 3)
        k = (lambda x, n, axis: torch.repeat_interleave(x, n, dim=axis))(k_cache, rep, axis=1)
        v = (lambda x, n, axis: torch.repeat_interleave(x, n, dim=axis))(v_cache, rep, axis=1)
        scores = torch.einsum("bhqd,bhkd->bhqk", q, k) * (Dh ** -0.5)
        p = _softmax(scores, axis=-1)
        o = torch.einsum("bhqk,bhkd->bhqd", p, v)
        return (lambda x, *d: x.permute(*d))(o, 0, 2, 1, 3).reshape(B, Sq, Hq * Dh) @ wo

    def _B_ref(x, w1, b1, w2, b2):
        h = torch.einsum("bsd,df->bsf", x, w1) + b1
        zero = torch.zeros_like(h)
        r = torch.where(h > zero, h, zero)
        h = r * r
        out = torch.einsum("bsf,fd->bsd", h, w2) + b2
        return out

    x = A_x
    h = x + _A_ref(_layernorm(x, axis=-1), A_k_cache, A_v_cache, A_wq, A_wo)
    h2 = h + _B_ref(_layernorm(h, axis=-1), B_w1, B_b1, B_w2, B_b2)
    return h2
```

```cpp
#include <cuda_runtime.h>
#include <cuda_bf16.h>
#include <cuda.h>
#include <stdint.h>

namespace {

constexpr int D_MODEL = 512;
constexpr int NHEAD = 32;
constexpr int SK = 8192;
constexpr int DH = 128;
constexpr int FF = 1376;
constexpr int QCOLS = NHEAD * DH;

constexpr int NCTA = 128;
constexpr int KEYS_PER_CTA = SK / 2;
constexpr int TILE_KEYS = 64;
constexpr int TILE_BYTES = TILE_KEYS * DH * 2;
constexpr int NTILE = KEYS_PER_CTA / TILE_KEYS;
#define NST_ 12
#define NINIT_ 2
#define STAG_ 0
constexpr int NST = NST_;
constexpr int NINIT = NINIT_;
constexpr int NCONS = 256;
constexpr int NTHREADS = NCONS + 64;
constexpr int NMLP = FF / 32;
constexpr int KPRE = NST - 4;
constexpr int T_WQ = 0, T_K0 = 4, T_WO = T_K0 + KPRE, T_K1 = T_WO + 4, T_V = T_K1 + NTILE - KPRE, T_W1 = T_V + NTILE,
              T_W2 = T_W1 + 2, T_END = T_W2 + 2;

constexpr int OFF_RING = 0;
constexpr int OFF_SP = OFF_RING + NST * TILE_BYTES;
constexpr int OFF_PART = OFF_SP + KEYS_PER_CTA * 2;
constexpr int OFF_CS = OFF_PART + 8 * 64 * 4;
constexpr int OFF_XN = OFF_CS + 8 * 64 * 4;
constexpr int OFF_X = OFF_XN + 1024;
constexpr int O_STRIDE = 272;
constexpr int OFF_O = OFF_X + 2048 + 1024 + 64;
constexpr int OFF_Q = OFF_O + 4 * O_STRIDE;
constexpr int OFF_RED = OFF_Q + 256;
constexpr int OFF_STAT = OFF_RED + 64;
constexpr int OFF_HID = OFF_STAT + 128;
constexpr int OFF_ML = OFF_HID + 160;
constexpr int OFF_BAR = OFF_ML + 16;
constexpr int SMEM_USED = OFF_BAR + (2 * NST + 4) * 8;
constexpr int SMEM_BYTES = SMEM_USED + 1024;

constexpr float FX_SCALE = 1073741824.0f;
constexpr float FX_INV = 1.0f / 1073741824.0f;

__device__ unsigned long long g_acc1[2 * D_MODEL];
constexpr int NFIN = 32;
__device__ uint4 g_part[NFIN * NMLP * 8];
__device__ unsigned int g_ticket[8 * 32];

#define TSTAMP(i)

__device__ __forceinline__ void mbar_init(uint32_t bar, uint32_t cnt) {
    asm volatile("mbarrier.init.shared::cta.b64 [%0], %1;" ::"r"(bar), "r"(cnt) : "memory");
}
__device__ __forceinline__ void mbar_expect_tx(uint32_t bar, uint32_t bytes) {
    asm volatile("mbarrier.arrive.expect_tx.shared::cta.b64 _, [%0], %1;" ::"r"(bar), "r"(bytes) : "memory");
}
__device__ __forceinline__ void mbar_arrive(uint32_t bar) {
    asm volatile("mbarrier.arrive.shared::cta.b64 _, [%0];" ::"r"(bar) : "memory");
}
__device__ __forceinline__ bool mbar_try(uint32_t bar, uint32_t parity) {
    uint32_t ok;
    asm volatile("{\n.reg .pred p;\nmbarrier.try_wait.parity.shared::cta.b64 p, [%1], %2;\nselp.u32 %0, 1, 0, p;\n}"
                 : "=r"(ok) : "r"(bar), "r"(parity) : "memory");
    return ok;
}
constexpr int SPIN_LIMIT = 1 << 20;
__device__ __forceinline__ void mbar_wait(uint32_t bar, uint32_t parity) {
    int n = 0;
    while (!mbar_try(bar, parity)) { if (++n > SPIN_LIMIT) __trap(); }
}
__device__ __forceinline__ void bulk_load(uint32_t dst, const void* src, uint32_t bytes, uint32_t bar) {
    asm volatile("cp.async.bulk.shared::cluster.global.mbarrier::complete_tx::bytes [%0], [%1], %2, [%3];"
                 ::"r"(dst), "l"(src), "r"(bytes), "r"(bar) : "memory");
}
__device__ __forceinline__ void tma2d(uint32_t dst, const CUtensorMap* tm, int c0, int c1, uint32_t bar) {
    asm volatile("cp.async.bulk.tensor.2d.shared::cluster.global.mbarrier::complete_tx::bytes [%0], [%1, {%3, %4}], [%2];"
                 ::"r"(dst), "l"(tm), "r"(bar), "r"(c0), "r"(c1) : "memory");
}
#define PF_ 1
#define DLY2_ 400
#define DLY1_ 150
#define GSLEEP_ 0
#define WLATE_ 1
#define WTH_ 40
#define POLL1_ 1
#define POLL2_ 1
#define STAG1_ 280
#define STAG2_ 280
#define EVF_ 1
__device__ __forceinline__ void bulk_load_stream(uint32_t dst, const void* src, uint32_t bytes, uint32_t bar, uint64_t pol) {
    asm volatile("cp.async.bulk.shared::cluster.global.mbarrier::complete_tx::bytes.L2::cache_hint [%0], [%1], %2, [%3], %4;"
                 ::"r"(dst), "l"(src), "r"(bytes), "r"(bar), "l"(pol) : "memory");
}
__device__ __forceinline__ void tma2d_stream(uint32_t dst, const CUtensorMap* tm, int c0, int c1, uint32_t bar, uint64_t pol) {
    asm volatile("cp.async.bulk.tensor.2d.shared::cluster.global.mbarrier::complete_tx::bytes.L2::cache_hint [%0], [%1, {%3, %4}], [%2], %5;"
                 ::"r"(dst), "l"(tm), "r"(bar), "r"(c0), "r"(c1), "l"(pol) : "memory");
}
__device__ __forceinline__ void cons_sync() { asm volatile("bar.sync 1, 256;" ::: "memory"); }

__device__ __forceinline__ uint32_t mapa(uint32_t addr, uint32_t rank) {
    uint32_t r;
    asm("mapa.shared::cluster.u32 %0, %1, %2;" : "=r"(r) : "r"(addr), "r"(rank));
    return r;
}
__device__ __forceinline__ void st_async_b32(uint32_t addr, uint32_t v, uint32_t bar) {
    asm volatile("st.async.weak.shared::cluster.mbarrier::complete_tx::bytes.b32 [%0], %1, [%2];" ::"r"(addr), "r"(v), "r"(bar) : "memory");
}
__device__ __forceinline__ void st_async_v2(uint32_t addr, uint32_t v0, uint32_t v1, uint32_t bar) {
    asm volatile("st.async.weak.shared::cluster.mbarrier::complete_tx::bytes.v2.b32 [%0], {%1, %2}, [%3];" ::"r"(addr), "r"(v0), "r"(v1), "r"(bar) : "memory");
}

__device__ __forceinline__ void mma_bf16(float (&d)[4], uint32_t a0, uint32_t a1, uint32_t a2, uint32_t a3, uint32_t b0, uint32_t b1) {
    asm volatile("mma.sync.aligned.m16n8k16.row.col.f32.bf16.bf16.f32 {%0,%1,%2,%3}, {%4,%5,%6,%7}, {%8,%9}, {%0,%1,%2,%3};"
                 : "+f"(d[0]), "+f"(d[1]), "+f"(d[2]), "+f"(d[3])
                 : "r"(a0), "r"(a1), "r"(a2), "r"(a3), "r"(b0), "r"(b1));
}
__device__ __forceinline__ void ldsm4(uint32_t (&r)[4], uint32_t addr) {
    asm volatile("ldmatrix.sync.aligned.m8n8.x4.shared.b16 {%0,%1,%2,%3}, [%4];"
                 : "=r"(r[0]), "=r"(r[1]), "=r"(r[2]), "=r"(r[3]) : "r"(addr) : "memory");
}
__device__ __forceinline__ void ldsm4t(uint32_t (&r)[4], uint32_t addr) {
    asm volatile("ldmatrix.sync.aligned.m8n8.x4.trans.shared.b16 {%0,%1,%2,%3}, [%4];"
                 : "=r"(r[0]), "=r"(r[1]), "=r"(r[2]), "=r"(r[3]) : "r"(addr) : "memory");
}
__device__ __forceinline__ uint4 lds128(uint32_t a) {
    uint4 v;
    asm volatile("ld.shared.v4.u32 {%0,%1,%2,%3}, [%4];" : "=r"(v.x), "=r"(v.y), "=r"(v.z), "=r"(v.w) : "r"(a) : "memory");
    return v;
}
__device__ __forceinline__ uint2 lds64(uint32_t a) {
    uint2 v;
    asm volatile("ld.shared.v2.u32 {%0,%1}, [%2];" : "=r"(v.x), "=r"(v.y) : "r"(a) : "memory");
    return v;
}
__device__ __forceinline__ uint32_t lds32(uint32_t a) {
    uint32_t v;
    asm volatile("ld.shared.u32 %0, [%1];" : "=r"(v) : "r"(a) : "memory");
    return v;
}
__device__ __forceinline__ void sts128(uint32_t a, uint4 v) {
    asm volatile("st.shared.v4.u32 [%0], {%1,%2,%3,%4};" ::"r"(a), "r"(v.x), "r"(v.y), "r"(v.z), "r"(v.w) : "memory");
}
__device__ __forceinline__ void sts64(uint32_t a, uint32_t v0, uint32_t v1) {
    asm volatile("st.shared.v2.u32 [%0], {%1,%2};" ::"r"(a), "r"(v0), "r"(v1) : "memory");
}
__device__ __forceinline__ void sts32(uint32_t a, uint32_t v) {
    asm volatile("st.shared.u32 [%0], %1;" ::"r"(a), "r"(v) : "memory");
}
__device__ __forceinline__ void sts16(uint32_t a, uint16_t v) {
    asm volatile("st.shared.u16 [%0], %1;" ::"r"(a), "h"(v) : "memory");
}
__device__ __forceinline__ float bf_lo(uint32_t v) { return __uint_as_float(v << 16); }
__device__ __forceinline__ float bf_hi(uint32_t v) { return __uint_as_float(v & 0xffff0000u); }
__device__ __forceinline__ uint32_t pack_bf(float lo, float hi) {
    uint32_t r;
    asm("cvt.rn.bf16x2.f32 %0, %1, %2;" : "=r"(r) : "f"(hi), "f"(lo));
    return r;
}
__device__ __forceinline__ float rnd_bf(float v) { return bf_lo(pack_bf(v, 0.f)); }

__device__ __forceinline__ unsigned long long fx_encode(float v) {
    return ((unsigned long long)__float2ll_rn(v * FX_SCALE) << 8) + 1ull;
}
__device__ __forceinline__ float fx_decode(uint32_t lo, uint32_t hi) {
    return fmaf(__int2float_rn((int)hi), 1.0f / 64.0f, __uint2float_rn(lo & 0xffffff00u) * (FX_INV / 256.0f));
}
__device__ __forceinline__ void spin_cycles(uint32_t n) {
    uint32_t t0, t;
    asm volatile("mov.u32 %0, %%clock;" : "=r"(t0));
    do { asm volatile("mov.u32 %0, %%clock;" : "=r"(t)); } while (t - t0 < n);
}
__device__ __forceinline__ void red_add64(unsigned long long* p, unsigned long long v) {
    asm volatile("red.relaxed.gpu.global.add.u64 [%0], %1;" ::"l"(p), "l"(v) : "memory");
}
__device__ __forceinline__ void ld_relaxed2x64(uint4& v, const void* p) {
    asm volatile("{\n.reg .b64 a, b;\nld.relaxed.gpu.global.v2.b64 {a, b}, [%4];\nmov.b64 {%0, %1}, a;\nmov.b64 {%2, %3}, b;\n}"
                 : "=r"(v.x), "=r"(v.y), "=r"(v.z), "=r"(v.w) : "l"(p) : "memory");
}
__device__ __forceinline__ void ld_relaxed128(uint4& v, const uint4* p) {
    asm volatile("ld.relaxed.gpu.global.v4.u32 {%0,%1,%2,%3}, [%4];" : "=r"(v.x), "=r"(v.y), "=r"(v.z), "=r"(v.w) : "l"(p) : "memory");
}
__device__ __forceinline__ uint32_t and3(uint32_t a, uint32_t b, uint32_t c) {
    uint32_t r;
    asm("lop3.b32 %0, %1, %2, %3, 0x80;" : "=r"(r) : "r"(a), "r"(b), "r"(c));
    return r;
}
__device__ __forceinline__ bool all_marked(const uint4& a, const uint4& b) {
    return __all_sync(~0u, and3(and3(a.x, a.y, a.z), and3(a.w, b.x, b.y), and3(b.z, b.w, 1u)));
}
__device__ __forceinline__ bool all_complete(const uint4& a, const uint4& b) {
    return __all_sync(~0u, and3(and3(a.x, a.z, b.x), b.z, 32u));
}
__device__ __forceinline__ void keep(const uint4& v, uint32_t addr, int never) {
    asm volatile("{\n.reg .pred p;\nsetp.ne.s32 p, %5, 0;\n@p st.shared.v4.u32 [%0], {%1,%2,%3,%4};\n}"
                 ::"r"(addr), "r"(v.x), "r"(v.y), "r"(v.z), "r"(v.w), "r"(never) : "memory");
}
__device__ __forceinline__ float bf16_at(uint32_t a) {
    uint16_t v;
    asm volatile("ld.shared.u16 %0, [%1];" : "=h"(v) : "r"(a) : "memory");
    return __uint_as_float((uint32_t)v << 16);
}
__device__ __forceinline__ unsigned ld_relaxed32(const unsigned* p) {
    unsigned v;
    asm volatile("ld.relaxed.gpu.global.u32 %0, [%1];" : "=r"(v) : "l"(p) : "memory");
    return v;
}

__device__ __forceinline__ int bpos(int k) { return ((k >> 1) & 3) * 16 + ((k >> 4) & 3) * 4 + ((k >> 3) & 1) * 2 + (k & 1); }

__device__ __forceinline__ void gemv1_partial(const uint32_t* a1, uint32_t hb0, uint32_t hb1, int j, int c, uint32_t a) {
    float t0[4] = {0.f, 0.f, 0.f, 0.f}, t1[4] = {0.f, 0.f, 0.f, 0.f}, t2[4] = {0.f, 0.f, 0.f, 0.f}, t3[4] = {0.f, 0.f, 0.f, 0.f};
#pragma unroll
    for (int k = 0; k < 2; k++) {
        const uint32_t m0 = (j == k) ? hb0 : 0u, m1 = (j == k) ? hb1 : 0u;
        const uint32_t n0 = (j == k + 2) ? hb0 : 0u, n1 = (j == k + 2) ? hb1 : 0u;
        mma_bf16(t0, a1[8 * k], a1[8 * k + 1], a1[8 * k + 2], a1[8 * k + 3], m0, m1);
        mma_bf16(t1, a1[8 * k + 4], a1[8 * k + 5], a1[8 * k + 6], a1[8 * k + 7], m0, m1);
        mma_bf16(t2, a1[8 * k + 16], a1[8 * k + 17], a1[8 * k + 18], a1[8 * k + 19], n0, n1);
        mma_bf16(t3, a1[8 * k + 20], a1[8 * k + 21], a1[8 * k + 22], a1[8 * k + 23], n0, n1);
    }
    const bool up2 = c & 2, up1 = c & 1;
    float r4[4], r2[2];
    const float send[4] = {up2 ? t2[0] : t0[1], up2 ? t2[2] : t0[3], up2 ? t3[0] : t1[1], up2 ? t3[2] : t1[3]};
    const float keep[4] = {up2 ? t2[1] : t0[0], up2 ? t2[3] : t0[2], up2 ? t3[1] : t1[0], up2 ? t3[3] : t1[2]};
#pragma unroll
    for (int i = 0; i < 4; i++) r4[i] = keep[i] + __shfl_xor_sync(~0u, send[i], 2);
#pragma unroll
    for (int i = 0; i < 2; i++) r2[i] = (up1 ? r4[i + 2] : r4[i]) + __shfl_xor_sync(~0u, up1 ? r4[i] : r4[i + 2], 1);
    sts32(a, __float_as_uint(r2[0]));
    sts32(a + 32, __float_as_uint(r2[1]));
}

__device__ __forceinline__ float sum8(uint32_t a) {
    float p[8];
#pragma unroll
    for (int w = 0; w < 8; w++) p[w] = __uint_as_float(lds32(a + w * 256));
    return ((p[0] + p[1]) + (p[2] + p[3])) + ((p[4] + p[5]) + (p[6] + p[7]));
}

struct Maps { CUtensorMap v, wq, wo, w1, w2; };

__global__ void __cluster_dims__(2, 1, 1) __launch_bounds__(NTHREADS, 1)
decode_block_kernel(const __grid_constant__ Maps tm,
                    const __nv_bfloat16* __restrict__ x, const __nv_bfloat16* __restrict__ Kc,
                    const __nv_bfloat16* __restrict__ b1, const __nv_bfloat16* __restrict__ b2,
                    __nv_bfloat16* __restrict__ out) {
    extern __shared__ unsigned char smem_raw[];
    const uint32_t sb = ((uint32_t)__cvta_generic_to_shared(smem_raw) + 1023u) & ~1023u;
    const uint32_t bar_full = sb + OFF_BAR, bar_empty = bar_full + NST * 8;
    const uint32_t bar_q = bar_empty + NST * 8, bar_ml = bar_q + 8, bar_o = bar_ml + 8, bar_x = bar_o + 8;

    int tid = threadIdx.x;
    asm volatile("" : "+r"(tid));
    const int lane = tid & 31;
    const int warp = __shfl_sync(~0u, tid >> 5, 0);
    const int bh = blockIdx.x >> 1, rank = blockIdx.x & 1;
    const int b = bh >> 5, h = bh & 31;
    const bool is_mlp = (rank == 0) && (bh < NMLP);
    const int f0 = bh * 32;

    if (warp == 8) {
        uint64_t pol;
        asm volatile("createpolicy.fractional.L2::evict_first.b64 %0, 1.0;" : "=l"(pol));
        const char* ksrc = (const char*)Kc + ((size_t)bh * SK + (size_t)rank * KEYS_PER_CTA) * (DH * 2);
        if (lane == 0) {
#pragma unroll
            for (int s = 0; s < NST; s++) { mbar_init(bar_full + s * 8, 1); mbar_init(bar_empty + s * 8, 8); }
            mbar_init(bar_q, 2); mbar_init(bar_ml, 1); mbar_init(bar_o, 10); mbar_init(bar_x, 1);
            asm volatile("fence.mbarrier_init.release.cluster;" ::: "memory");
            mbar_expect_tx(bar_x, is_mlp ? 2048 + 1024 + 64 : 2048);
            bulk_load(sb + OFF_X, x, 2048, bar_x);
            if (is_mlp) {
                bulk_load(sb + OFF_X + 2048, b2, 1024, bar_x);
                bulk_load(sb + OFF_X + 3072, b1 + f0, 64, bar_x);
            }
#pragma unroll
            for (int s = 0; s < T_K0 + NINIT; s++) {
                const uint32_t dst = sb + OFF_RING + s * TILE_BYTES, fb = bar_full + s * 8;
                mbar_expect_tx(fb, TILE_BYTES);
                if (s < T_K0) tma2d(dst, &tm.wq, h * DH + rank * 64, (s - T_WQ) * 128, fb);
                else bulk_load_stream(dst, ksrc + (size_t)(s - T_K0) * TILE_BYTES, TILE_BYTES, fb, pol);
            }
            mbar_expect_tx(bar_q, 128);
            mbar_expect_tx(bar_ml, 8);
            mbar_expect_tx(bar_o, 512);
            asm volatile("prefetch.tensormap [%0];" ::"l"(&tm.wo) : "memory");
            asm volatile("prefetch.tensormap [%0];" ::"l"(&tm.v) : "memory");
            asm volatile("prefetch.tensormap [%0];" ::"l"(&tm.w1) : "memory");
            asm volatile("prefetch.tensormap [%0];" ::"l"(&tm.w2) : "memory");
        }
        __syncwarp();
        asm volatile("barrier.cluster.arrive.relaxed.aligned;" ::: "memory");
        asm volatile("barrier.cluster.wait.aligned;" ::: "memory");
        if (lane == 0) {
            int nk = NINIT;
#pragma unroll
            for (int w = 0; w < 4; w++) {
                mbar_wait(bar_full + w * 8, 0);
                const int upto = (w == 3) ? KPRE : min(KPRE, NINIT + STAG_ * (w + 1));
#pragma unroll 1
                for (; nk < upto; nk++) {
                    const uint32_t fb = bar_full + (T_K0 + nk) * 8;
                    mbar_expect_tx(fb, TILE_BYTES);
                    bulk_load_stream(sb + OFF_RING + (T_K0 + nk) * TILE_BYTES, ksrc + (size_t)nk * TILE_BYTES, TILE_BYTES, fb, pol);
                }
            }
            const int vline0 = (bh * SK + rank * KEYS_PER_CTA) * 2;
            const int tend = is_mlp ? T_END : T_W1;
            int st = 0, ph = 0;
#pragma unroll 1
            for (int t = NST; t < tend; t++) {
                const uint32_t dst = sb + OFF_RING + st * TILE_BYTES, fb = bar_full + st * 8;
                mbar_wait(bar_empty + st * 8, ph);
                if (t == T_W1) {
                    if (WLATE_ < 8) mbar_wait(bar_full + ((T_W1 - 1 - WLATE_) % NST) * 8, ((T_W1 - 1 - WLATE_) / NST) & 1);
                    if (WTH_) {
                        int n = 0;
                        while (ld_relaxed32(g_ticket) < (unsigned)WTH_) { __nanosleep(100); if (++n > SPIN_LIMIT) __trap(); }
                    }
                }
                mbar_expect_tx(fb, TILE_BYTES);
                if (t < T_K1) {
                    tma2d(dst, &tm.wo, rank * 256 + (t - T_WO) * 64, h * DH, fb);
                } else if (t < T_V) {
                    bulk_load_stream(dst, ksrc + (size_t)(t - 8) * TILE_BYTES, TILE_BYTES, fb, pol);
                } else if (t < T_W1) {
                    tma2d_stream(dst, &tm.v, 0, vline0 + (t - T_V) * (TILE_KEYS * 2), fb, pol);
                } else if (t < T_W2) {
                    tma2d(dst, &tm.w1, f0, (t - T_W1) * 256, fb);
                } else {
#pragma unroll
                    for (int i = 0; i < 4; i++) tma2d(dst + i * 4096, &tm.w2, ((t - T_W2) * 4 + i) * 64, f0, fb);
                }
                if (++st == NST) { st = 0; ph ^= 1; }
            }
        }
        return;
    }

    if (warp == 9) {
        asm volatile("barrier.cluster.arrive.relaxed.aligned;" ::: "memory");
        if (is_mlp) {
#pragma unroll
            for (int i = 0; i < 8; i++) g_part[((i * 4 + (lane >> 3)) * NMLP + bh) * 8 + (lane & 7)] = make_uint4(0, 0, 0, 0);
            __threadfence();
        }
        asm volatile("barrier.cluster.wait.aligned;" ::: "memory");
        if (lane == 0) mbar_arrive(bar_o);
        return;
    }

    const int g = lane >> 2, c = lane & 3;
    const int rr = lane & 7, mi = lane >> 3;
    TSTAMP(0);
    asm volatile("barrier.cluster.arrive.relaxed.aligned;" ::: "memory");
    const int mb_ = g & 1, j4 = g >> 1;
    const int d0 = warp * 64 + j4 * 16 + c * 2;
    uint32_t qa[16], wf[64];
    {
        asm volatile("barrier.cluster.wait.aligned;" ::: "memory");
        mbar_wait(bar_x, 0);
        const uint4 xa0 = lds128(sb + OFF_X + b * 1024 + lane * 16), xa1 = lds128(sb + OFF_X + b * 1024 + 512 + lane * 16);
        const uint32_t xp = lds32(sb + OFF_X + b * 1024 + tid * 4);
        const uint32_t xa[8] = {xa0.x, xa0.y, xa0.z, xa0.w, xa1.x, xa1.y, xa1.z, xa1.w};
        float s = 0.f;
#pragma unroll
        for (int i = 0; i < 8; i++) s += bf_lo(xa[i]) + bf_hi(xa[i]);
#pragma unroll
        for (int o = 16; o; o >>= 1) s += __shfl_xor_sync(~0u, s, o);
        const float mean = s * (1.0f / D_MODEL);
        float v = 0.f;
#pragma unroll
        for (int i = 0; i < 8; i++) { const float e0 = bf_lo(xa[i]) - mean, e1 = bf_hi(xa[i]) - mean; v += e0 * e0 + e1 * e1; }
#pragma unroll
        for (int o = 16; o; o >>= 1) v += __shfl_xor_sync(~0u, v, o);
        const float mb = rnd_bf(mean);
        const float den = rnd_bf(sqrtf(rnd_bf(rnd_bf(v * (1.0f / D_MODEL)) + 1e-5f)));
        sts32(sb + OFF_XN + (((tid * 2) & ~63) + bpos(tid * 2)) * 2,
              pack_bf(__fdiv_rn(rnd_bf(bf_lo(xp) - mb), den), __fdiv_rn(rnd_bf(bf_hi(xp) - mb), den)));
        TSTAMP(12);
        cons_sync();

        float q0[4] = {0.f, 0.f, 0.f, 0.f}, q1[4] = {0.f, 0.f, 0.f, 0.f};
        const uint32_t aoff = ((warp >> 2) * 64 + (mi >> 1) * 8 + rr) * 128 + (((warp & 3) * 2 + (mi & 1)) ^ rr) * 16;
#pragma unroll
        for (int t = 0; t < 4; t++) {
            const uint32_t xaddr = sb + OFF_XN + (t * 2 + (warp >> 2)) * 128 + c * 32;
            const uint4 p0 = lds128(xaddr), p1 = lds128(xaddr + 16);
            const uint32_t base = sb + OFF_RING + (T_WQ + t) * TILE_BYTES + aoff;
            mbar_wait(bar_full + (T_WQ + t) * 8, 0);
            uint32_t a0[4], a1[4], a2[4], a3[4];
            ldsm4t(a0, base); ldsm4t(a1, base + 2048); ldsm4t(a2, base + 4096); ldsm4t(a3, base + 6144);
            mma_bf16(q0, a0[0], a0[1], a0[2], a0[3], p0.x, p0.y);
            mma_bf16(q1, a1[0], a1[1], a1[2], a1[3], p0.z, p0.w);
            mma_bf16(q0, a2[0], a2[1], a2[2], a2[3], p1.x, p1.y);
            mma_bf16(q1, a3[0], a3[1], a3[2], a3[3], p1.z, p1.w);
            __syncwarp();
            if (lane == 0) mbar_arrive(bar_empty + (T_WQ + t) * 8);
        }
        TSTAMP(13);
        if (c < 2) sts32(sb + OFF_PART + (warp * 16 + c * 8 + g) * 4, __float_as_uint(c ? q0[2] + q1[2] : q0[0] + q1[0]));
        cons_sync();
        if (warp == 0) {
            const uint2 u = lds64(sb + OFF_PART + lane * 8), w = lds64(sb + OFF_PART + 256 + lane * 8);
            const uint32_t qq = pack_bf(__uint_as_float(u.x) + __uint_as_float(w.x), __uint_as_float(u.y) + __uint_as_float(w.y));
            const uint32_t dst = sb + OFF_Q + rank * 128 + lane * 4;
            sts32(dst, qq);
            st_async_b32(mapa(dst, rank ^ 1), qq, mapa(bar_q, rank ^ 1));
            __syncwarp();
            if (lane == 0) mbar_arrive(bar_q);
        }
        mbar_wait(bar_q, 0);
#pragma unroll
        for (int j = 0; j < 16; j++) qa[j] = lds32(sb + OFF_Q + ((j & 8) + ((g + j) & 7)) * 16 + c * 4);
    }
    TSTAMP(1);

    int st = T_K0, ph = 0;
    float mx = -INFINITY;
    {
        uint32_t koff0 = sb + OFF_RING + (warp * 8 + rr) * 256 + ((rr + mi) & 7) * 16;
        uint32_t koff1 = sb + OFF_RING + (warp * 8 + rr) * 256 + ((rr + mi + 4) & 7) * 16;
        asm volatile("" : "+r"(koff0), "+r"(koff1));
        const bool valid = (c == (g >> 1));
        uint32_t spos = sb + OFF_SP + bpos(warp * 8 + g) * 2;
        auto k_tiles = [&](int n) {
#pragma unroll 1
            for (int i = 0; i < n; i++) {
                const uint32_t base = st * TILE_BYTES;
                mbar_wait(bar_full + st * 8, ph);
                uint32_t k0[4], k1[4], k2[4], k3[4];
                ldsm4(k0, base + koff0); ldsm4(k1, base + koff1);
                ldsm4(k2, base + koff0 + 128); ldsm4(k3, base + koff1 + 128);
                float s0[4] = {0.f, 0.f, 0.f, 0.f}, s1[4] = {0.f, 0.f, 0.f, 0.f};
                mma_bf16(s0, qa[0], qa[2], qa[1], qa[3], k0[0], k0[1]);
                mma_bf16(s1, qa[0], qa[2], qa[1], qa[3], k0[2], k0[3]);
                mma_bf16(s0, qa[4], qa[6], qa[5], qa[7], k1[0], k1[1]);
                mma_bf16(s1, qa[4], qa[6], qa[5], qa[7], k1[2], k1[3]);
                mma_bf16(s0, qa[8], qa[10], qa[9], qa[11], k2[0], k2[1]);
                mma_bf16(s1, qa[8], qa[10], qa[9], qa[11], k2[2], k2[3]);
                mma_bf16(s0, qa[12], qa[14], qa[13], qa[15], k3[0], k3[1]);
                mma_bf16(s1, qa[12], qa[14], qa[13], qa[15], k3[2], k3[3]);
                __syncwarp();
                if (lane == 0) mbar_arrive(bar_empty + st * 8);
                const float raw = (g & 1) ? s0[1] + s1[3] : s0[0] + s1[2];
                const uint32_t sc = pack_bf(rnd_bf(raw) * 0.08838834764831845f, 0.f);
                if (valid) { sts16(spos, (uint16_t)sc); mx = fmaxf(mx, bf_lo(sc)); }
                spos += TILE_KEYS * 2;
                if (++st == NST) { st = 0; ph ^= 1; }
            }
        };
        k_tiles(KPRE);
        {
            static_assert(T_WO == NST, "wo tiles sit in slots 0..3, second pass");
            const int s = warp >> 1;
            const int row = (mi >> 1) * 4 + (rr >> 1) + (rr & 1) * 8;
            const uint32_t base = sb + OFF_RING + s * TILE_BYTES + row * 128;
            const uint32_t c0 = (((mi & 1) * 2 + (warp & 1)) ^ (row & 7)) * 16, c1 = c0 ^ 64;
            mbar_wait(bar_full + s * 8, 1);
#pragma unroll
            for (int t = 0; t < 8; t++) {
                ldsm4t(*(uint32_t(*)[4])(wf + 8 * t), base + t * 2048 + c0);
                ldsm4t(*(uint32_t(*)[4])(wf + 8 * t + 4), base + t * 2048 + c1);
            }
            __syncwarp();
            if (lane < 4) mbar_arrive(bar_empty + lane * 8);
            st = 4;
        }
        k_tiles(NTILE - KPRE);
    }
    TSTAMP(2);
    {
#pragma unroll
        for (int o = 16; o; o >>= 1) mx = fmaxf(mx, __shfl_xor_sync(~0u, mx, o));
        if (lane == 0) sts32(sb + OFF_RED + warp * 4, __float_as_uint(mx));
        cons_sync();
        const uint4 m0 = lds128(sb + OFF_RED), m1 = lds128(sb + OFF_RED + 16);
        const float mloc = fmaxf(fmaxf(fmaxf(__uint_as_float(m0.x), __uint_as_float(m0.y)), fmaxf(__uint_as_float(m0.z), __uint_as_float(m0.w))),
                                 fmaxf(fmaxf(__uint_as_float(m1.x), __uint_as_float(m1.y)), fmaxf(__uint_as_float(m1.z), __uint_as_float(m1.w))));
        const uint4 s0 = lds128(sb + OFF_SP + tid * 16), s1 = lds128(sb + OFF_SP + 4096 + tid * 16);
        const uint32_t sv[8] = {s0.x, s0.y, s0.z, s0.w, s1.x, s1.y, s1.z, s1.w};
        constexpr float LOG2E = 1.4426950408889634f;
        float l = 0.f;
#pragma unroll
        for (int i = 0; i < 8; i++) l += exp2f((bf_lo(sv[i]) - mloc) * LOG2E) + exp2f((bf_hi(sv[i]) - mloc) * LOG2E);
#pragma unroll
        for (int o = 16; o; o >>= 1) l += __shfl_xor_sync(~0u, l, o);
        if (lane == 0) sts32(sb + OFF_RED + 32 + warp * 4, __float_as_uint(l));
        cons_sync();
        const uint4 l0 = lds128(sb + OFF_RED + 32), l1 = lds128(sb + OFF_RED + 48);
        const float lloc = ((__uint_as_float(l0.x) + __uint_as_float(l0.y)) + (__uint_as_float(l0.z) + __uint_as_float(l0.w))) +
                           ((__uint_as_float(l1.x) + __uint_as_float(l1.y)) + (__uint_as_float(l1.z) + __uint_as_float(l1.w)));
        if (tid == 0) st_async_v2(mapa(sb + OFF_ML, rank ^ 1), __float_as_uint(mloc), __float_as_uint(lloc), mapa(bar_ml, rank ^ 1));
        mbar_wait(bar_ml, 0);
        const uint2 pml = lds64(sb + OFF_ML);
        const float mp = __uint_as_float(pml.x), lp = __uint_as_float(pml.y);
        const float M = fmaxf(mloc, mp);
        const float m_a = rank ? mp : mloc, l_a = rank ? lp : lloc, m_b = rank ? mloc : mp, l_b = rank ? lloc : lp;
        const float L = l_a * exp2f((m_a - M) * LOG2E) + l_b * exp2f((m_b - M) * LOG2E);
        const float inv = 1.0f / L;
        uint32_t pv[8];
#pragma unroll
        for (int i = 0; i < 8; i++)
            pv[i] = pack_bf(exp2f((bf_lo(sv[i]) - M) * LOG2E) * inv, exp2f((bf_hi(sv[i]) - M) * LOG2E) * inv);
        sts128(sb + OFF_SP + tid * 16, make_uint4(pv[0], pv[1], pv[2], pv[3]));
        sts128(sb + OFF_SP + 4096 + tid * 16, make_uint4(pv[4], pv[5], pv[6], pv[7]));
        cons_sync();
    }
    TSTAMP(3);
    unsigned long long* acc1_dst = g_acc1 + b * D_MODEL + rank * 256 + warp * 32 + c * 8 + g;
    unsigned* ticket_dst = g_ticket + (tid & 7) * 32;
    uint32_t o_dst = sb + OFF_O + (rank * 2 + (c & 1)) * O_STRIDE + (warp * 8 + g) * 4, o_bar = bar_o;
    if (c & 2) { o_dst = mapa(o_dst, rank ^ 1); o_bar = mapa(bar_o, rank ^ 1); }
    uint32_t o_src = sb + OFF_O + (rr & 3) * O_STRIDE + mi * 16;
    asm volatile("" : "+l"(acc1_dst), "+l"(ticket_dst), "+r"(o_dst), "+r"(o_bar), "+r"(o_src));
    const bool is_fin = bh < NFIN;
    const unsigned* ticket_src = g_ticket + warp * 32;
    const unsigned long long* p1 = g_acc1 + mb_ * D_MODEL + warp * 64 + j4 * 8 + c * 2;
    uint4* part_dst = g_part + ((warp * 4 + c) * NMLP + bh) * 8 + g;
    const uint4* inbox = g_part + bh * (NMLP * 8) + tid;
    const uint4* inbox2 = tid < (NMLP - 32) * 8 ? inbox + 256 : inbox;
    const uint4* inbox_pf = g_part + (bh * NMLP + tid) * 8;
    int do_pf = is_fin && tid < NMLP;
    float wsel = tid < (NMLP - 32) * 8 ? 1.0f : 0.0f;
    __nv_bfloat16* out_dst = out + ((lane >> 3) & 1) * D_MODEL + bh * 16 + (lane >> 4) * 8 + (lane & 7);
    asm volatile("" : "+l"(ticket_src), "+l"(p1), "+l"(part_dst), "+l"(inbox), "+l"(inbox2), "+l"(inbox_pf), "+r"(do_pf), "+f"(wsel), "+l"(out_dst));
    uint32_t xv[2] = {lds32(sb + OFF_X + (mb_ * D_MODEL + d0) * 2), lds32(sb + OFF_X + (mb_ * D_MODEL + d0 + 8) * 2)};
    float b1v = bf16_at(sb + OFF_X + 3072 + lane * 2);
    float b2v = bf16_at(sb + OFF_X + 2048 + ((bh & 31) * 16 + (lane >> 4) * 8 + (lane & 7)) * 2);
    uint32_t a_part = sb + OFF_PART + warp * 256 + ((c >> 1) * 32 + (c & 1) * 16 + g) * 4;
    uint32_t a_stat = sb + OFF_STAT + (mb_ * 16 + (c & 1) * 8 + warp) * 4;
    uint32_t a_keep = sb + OFF_RED + mb_ * 32 + c * 4;
    uint32_t a_sum = sb + OFF_PART + (warp * 32 + lane) * 4, a_cs = sb + OFF_CS + lane * 4;
    uint32_t a_hid = sb + OFF_HID + warp * 80 + lane * 2, a_hidb = sb + OFF_HID + (rr & 1) * 80 + mi * 16;
    uint32_t a_fin = sb + OFF_PART + warp * 256 + lane * 4;
    uint32_t a_hfin = sb + OFF_RED + ((lane >> 3) & 1) * 32 + ((lane >> 4) * 8 + (lane & 7)) * 2;
    int keep_h = warp * 4 + j4 == bh;
    asm volatile("" : "+r"(a_part), "+r"(a_stat), "+r"(a_keep), "+r"(a_sum), "+r"(a_cs), "+r"(a_hid), "+r"(a_hidb), "+r"(a_fin), "+r"(a_hfin),
                 "+r"(keep_h), "+f"(b1v), "+f"(b2v));
    static_assert(T_W1 % NST + 3 < NST, "w1/w2 occupy four consecutive slots with the same parity");
    constexpr int W_PAR = (T_W1 / NST) & 1;
    uint32_t w1_bar = bar_full + (T_W1 % NST + (warp >> 2)) * 8;
    uint32_t w1_a = sb + OFF_RING + (T_W1 % NST + (warp >> 2)) * TILE_BYTES + ((warp & 3) * 64 + (mi >> 1) * 8 + rr) * 64 + ((mi & 1) ^ (rr >> 1)) * 16;
    uint32_t w2_a = sb + OFF_RING + (T_W2 % NST + (warp >> 2)) * TILE_BYTES + (warp & 3) * 4096 + ((mi >> 1) * 8 + rr) * 128 + ((mi & 1) ^ rr) * 16;
    asm volatile("" : "+r"(w1_bar), "+r"(w1_a), "+r"(w2_a));
    {
        const int hh = warp >> 2, ch = 2 * (warp & 3);
        const int line = 2 * (8 * (mi >> 1) + rr) + hh;
        uint32_t voff = sb + OFF_RING + line * 128 + (((ch ^ (mi & 1) ^ (rr >> 2)) ^ (line & 7)) * 16);
        uint32_t pmask = ((c >> 1) == (g & 1)) ? 0xffffffffu : 0u;
        asm volatile("" : "+r"(voff), "+r"(pmask));
        uint32_t paddr = sb + OFF_SP + c * 32;
        float o0[4] = {0.f, 0.f, 0.f, 0.f}, o1[4] = {0.f, 0.f, 0.f, 0.f};
#pragma unroll 1
        for (int i = 0; i < NTILE; i++) {
            const uint32_t base = voff + st * TILE_BYTES;
            uint4 p0 = lds128(paddr), p1 = lds128(paddr + 16);
            p0.x &= pmask; p0.y &= pmask; p0.z &= pmask; p0.w &= pmask;
            p1.x &= pmask; p1.y &= pmask; p1.z &= pmask; p1.w &= pmask;
            asm volatile("" : "+r"(p0.x), "+r"(p0.y), "+r"(p0.z), "+r"(p0.w), "+r"(p1.x), "+r"(p1.y), "+r"(p1.z), "+r"(p1.w));
            mbar_wait(bar_full + st * 8, ph);
            uint32_t a0[4], a1[4], a2[4], a3[4];
            ldsm4t(a0, base); ldsm4t(a1, base + 4096); ldsm4t(a2, base + 8192); ldsm4t(a3, base + 12288);
            if (i == NTILE - 1 && tid < 8) asm volatile("red.relaxed.gpu.global.add.u32 [%0], 1;" ::"l"(ticket_dst) : "memory");
            mma_bf16(o0, a0[0], a0[1], a0[2], a0[3], p0.x, p0.y);
            mma_bf16(o1, a1[0], a1[1], a1[2], a1[3], p0.z, p0.w);
            mma_bf16(o0, a2[0], a2[1], a2[2], a2[3], p1.x, p1.y);
            mma_bf16(o1, a3[0], a3[1], a3[2], a3[3], p1.z, p1.w);
            __syncwarp();
            if (lane == 0) mbar_arrive(bar_empty + st * 8);
            paddr += TILE_KEYS * 2;
            if (++st == NST) { st = 0; ph ^= 1; }
        }
        TSTAMP(4);
        const float v0 = (o0[0] + o1[0]) + (o0[3] + o1[3]);
        const float v1 = (o0[1] + o1[1]) + (o0[2] + o1[2]);
        const uint32_t hi = pack_bf(v0, v1);
        const uint32_t val = (c & 1) ? pack_bf(v0 - bf_lo(hi), v1 - bf_hi(hi)) : hi;
        if (c & 2) st_async_b32(o_dst, val, o_bar);
        else sts32(o_dst, val);
        __syncwarp();
        if (lane == 0) mbar_arrive(bar_o);
        mbar_wait(bar_o, 0);
    }
    TSTAMP(5);
    {
        float d00[4] = {0.f, 0.f, 0.f, 0.f}, d01[4] = {0.f, 0.f, 0.f, 0.f}, d10[4] = {0.f, 0.f, 0.f, 0.f}, d11[4] = {0.f, 0.f, 0.f, 0.f};
        uint32_t ob[4][4];
#pragma unroll
        for (int t = 0; t < 4; t++) ldsm4(ob[t], o_src + t * 64);
#pragma unroll
        for (int t = 0; t < 4; t++) {
            mma_bf16(d00, wf[16 * t], wf[16 * t + 1], wf[16 * t + 2], wf[16 * t + 3], ob[t][0], ob[t][1]);
            mma_bf16(d10, wf[16 * t + 4], wf[16 * t + 5], wf[16 * t + 6], wf[16 * t + 7], ob[t][0], ob[t][1]);
            mma_bf16(d01, wf[16 * t + 8], wf[16 * t + 9], wf[16 * t + 10], wf[16 * t + 11], ob[t][2], ob[t][3]);
            mma_bf16(d11, wf[16 * t + 12], wf[16 * t + 13], wf[16 * t + 14], wf[16 * t + 15], ob[t][2], ob[t][3]);
        }
        const float e0 = (d00[0] + d01[0]) + (d00[1] + d01[1]), e1 = (d00[2] + d01[2]) + (d00[3] + d01[3]);
        const float e2 = (d10[0] + d11[0]) + (d10[1] + d11[1]), e3 = (d10[2] + d11[2]) + (d10[3] + d11[3]);
        const float ea = (c & 2) ? e2 : e0, eb = (c & 2) ? e3 : e1;
        const float e = ((c & 1) ? eb : ea) + __shfl_xor_sync(~0u, (c & 1) ? ea : eb, 1);
        red_add64(acc1_dst, fx_encode(e));
    }
    TSTAMP(6);
    if (!is_mlp) return;

    {
        const int never = gridDim.x != NCTA;
        if (PF_ && do_pf) asm volatile("prefetch.global.L2 [%0];" ::"l"(inbox_pf));
        uint32_t* a1 = wf;
        uint32_t* a2 = wf + 32;
        mbar_wait(w1_bar, W_PAR);
#pragma unroll
        for (int k = 0; k < 4; k++) {
            ldsm4t(*(uint32_t(*)[4])(a1 + 8 * k), w1_a + k * 1024);
            ldsm4t(*(uint32_t(*)[4])(a1 + 8 * k + 4), (w1_a ^ 32) + k * 1024);
        }
        gemv1_partial(a1, 0x3f803f80u, 0x3f803f80u, j4, c, a_part + (OFF_CS - OFF_PART));
        TSTAMP(7);
        uint4 ua, ub, va = make_uint4(0, 0, 0, 0), vb = va;
        uint32_t hb0, hb1;
        {
            ld_relaxed2x64(ua, p1); ld_relaxed2x64(ub, p1 + 32);
            unsigned tk = ld_relaxed32(ticket_src);
            mbar_wait(w1_bar + 16, W_PAR);
#pragma unroll
            for (int u = 0; u < 2; u++)
#pragma unroll
                for (int T = 0; T < 4; T++) ldsm4t(*(uint32_t(*)[4])(a2 + 16 * u + 4 * T), (w2_a ^ (T * 32)) + u * 2048);
            int n = 0;
            if (tk < (unsigned)NCTA) {
                do {
                    if (GSLEEP_) __nanosleep(GSLEEP_);
                    tk = ld_relaxed32(ticket_src);
                    if (++n > SPIN_LIMIT) __trap();
                } while (tk < (unsigned)NCTA);
                if (PF_ && do_pf) asm volatile("prefetch.global.L2 [%0];" ::"l"(inbox_pf));
                if (DLY1_) spin_cycles(DLY1_);
                ld_relaxed2x64(ua, p1); ld_relaxed2x64(ub, p1 + 32);
                if (POLL1_ > 1) spin_cycles(STAG1_);
            }
            auto finish = [&](const uint4& a, const uint4& bb) {
                const uint32_t at0 = pack_bf(fx_decode(a.x, a.y), fx_decode(a.z, a.w)), at1 = pack_bf(fx_decode(bb.x, bb.y), fx_decode(bb.z, bb.w));
                hb0 = pack_bf(bf_lo(xv[0]) + bf_lo(at0), bf_hi(xv[0]) + bf_hi(at0));
                hb1 = pack_bf(bf_lo(xv[1]) + bf_lo(at1), bf_hi(xv[1]) + bf_hi(at1));
            };
            while (!all_complete(ua, ub)) {
                ld_relaxed2x64(ua, p1); ld_relaxed2x64(ub, p1 + 32);
                if (++n > SPIN_LIMIT) __trap();
            }
            finish(ua, ub);
        }
        TSTAMP(8);
        gemv1_partial(a1, hb0, hb1, j4, c, a_part);
        {
            const float h0 = bf_lo(hb0), h1 = bf_hi(hb0), h2 = bf_lo(hb1), h3 = bf_hi(hb1);
            const float s1 = (h0 + h1) + (h2 + h3);
            const float s2 = (h0 * h0 + h1 * h1) + (h2 * h2 + h3 * h3);
            float t = ((c & 1) ? s2 : s1) + __shfl_xor_sync(~0u, (c & 1) ? s1 : s2, 1);
            t += __shfl_xor_sync(~0u, t, 2);
            t += __shfl_xor_sync(~0u, t, 8);
            t += __shfl_xor_sync(~0u, t, 16);
            if ((lane & 0x1a) == 0) sts32(a_stat, __float_as_uint(t));
        }
        if (keep_h) {
            sts32(a_keep, hb0);
            sts32(a_keep + 16, hb1);
        }
        cons_sync();
        TSTAMP(9);
        if (warp < 2) {
            const uint4 q0 = lds128(sb + OFF_STAT + warp * 64), q1 = lds128(sb + OFF_STAT + warp * 64 + 16);
            const uint4 q2 = lds128(sb + OFF_STAT + warp * 64 + 32), q3 = lds128(sb + OFF_STAT + warp * 64 + 48);
            const float sacc = sum8(a_sum);
            const float cs = sum8(a_cs);
            const float mean = (((__uint_as_float(q0.x) + __uint_as_float(q0.y)) + (__uint_as_float(q0.z) + __uint_as_float(q0.w))) +
                                ((__uint_as_float(q1.x) + __uint_as_float(q1.y)) + (__uint_as_float(q1.z) + __uint_as_float(q1.w)))) * (1.0f / D_MODEL);
            const float msq = (((__uint_as_float(q2.x) + __uint_as_float(q2.y)) + (__uint_as_float(q2.z) + __uint_as_float(q2.w))) +
                               ((__uint_as_float(q3.x) + __uint_as_float(q3.y)) + (__uint_as_float(q3.z) + __uint_as_float(q3.w)))) * (1.0f / D_MODEL);
            const float var = fmaxf(msq - mean * mean, 0.f);
            float sq, iden;
            asm("sqrt.approx.ftz.f32 %0, %1;" : "=f"(sq) : "f"(rnd_bf(rnd_bf(var) + 1e-5f)));
            asm("rcp.approx.ftz.f32 %0, %1;" : "=f"(iden) : "f"(rnd_bf(sq)));
            const float z = fmaxf(rnd_bf(rnd_bf((sacc - rnd_bf(mean) * cs) * iden) + b1v), 0.f);
            sts16(a_hid, (uint16_t)pack_bf(z * z, 0.f));
        }
        cons_sync();
        uint32_t hb[4];
        ldsm4(hb, a_hidb);
        const float hfin = bf16_at(a_hfin);
        float y[4][4];
#pragma unroll
        for (int T = 0; T < 4; T++) {
            y[T][0] = y[T][1] = y[T][2] = y[T][3] = 0.f;
            mma_bf16(y[T], a2[4 * T], a2[4 * T + 1], a2[4 * T + 2], a2[4 * T + 3], hb[0], hb[1]);
        }
#pragma unroll
        for (int T = 0; T < 4; T++)
            mma_bf16(y[T], a2[16 + 4 * T], a2[16 + 4 * T + 1], a2[16 + 4 * T + 2], a2[16 + 4 * T + 3], hb[2], hb[3]);
        {
            const bool up2 = c & 2, up1 = c & 1;
            uint32_t e[4];
#pragma unroll
            for (int i = 0; i < 4; i++) e[i] = __float_as_uint(up2 ? (up1 ? y[3][i] : y[2][i]) : (up1 ? y[1][i] : y[0][i])) | 1u;
            asm volatile("st.relaxed.gpu.global.v4.u32 [%0], {%1,%2,%3,%4};" ::"l"(part_dst), "r"(e[0]), "r"(e[1]), "r"(e[2]), "r"(e[3]) : "memory");
        }
        TSTAMP(10);
        if (!is_fin) { keep(ua, sb, never); keep(ub, sb, never); keep(va, sb, never); keep(vb, sb, never); return; }
        uint4 u, w, u2 = make_uint4(0, 0, 0, 0), w2 = u2;
        {
            float v0, v1, v2, v3;
            auto finish = [&](const uint4& a, const uint4& bb) {
                v0 = fmaf(__uint_as_float(bb.x), wsel, __uint_as_float(a.x)); v1 = fmaf(__uint_as_float(bb.y), wsel, __uint_as_float(a.y));
                v2 = fmaf(__uint_as_float(bb.z), wsel, __uint_as_float(a.z)); v3 = fmaf(__uint_as_float(bb.w), wsel, __uint_as_float(a.w));
            };
            int n = 0;
            if (DLY2_) spin_cycles(DLY2_);
            ld_relaxed128(u, inbox); ld_relaxed128(w, inbox2);
            while (!all_marked(u, w)) {
                ld_relaxed128(u, inbox); ld_relaxed128(w, inbox2);
                if (++n > SPIN_LIMIT) __trap();
            }
            finish(u, w);
            const bool up16 = lane & 16, up8 = lane & 8;
            const float r0 = (up16 ? v2 : v0) + __shfl_xor_sync(~0u, up16 ? v0 : v2, 16);
            const float r1 = (up16 ? v3 : v1) + __shfl_xor_sync(~0u, up16 ? v1 : v3, 16);
            const float r = (up8 ? r1 : r0) + __shfl_xor_sync(~0u, up8 ? r0 : r1, 8);
            sts32(a_fin, __float_as_uint(r));
        }
        cons_sync();
        if (warp == 0) {
            const float y2 = sum8(a_sum);
            *out_dst = __ushort_as_bfloat16((unsigned short)pack_bf(hfin + rnd_bf(rnd_bf(y2) + b2v), 0.f));
        }
        if (bh == 0) {
            *(ulonglong2*)(g_acc1 + tid * 4) = make_ulonglong2(0, 0);
            *(ulonglong2*)(g_acc1 + tid * 4 + 2) = make_ulonglong2(0, 0);
            g_ticket[tid] = 0;
        }
        keep(ua, sb, never); keep(ub, sb, never); keep(va, sb, never); keep(vb, sb, never); keep(u, sb, never); keep(w, sb, never); keep(u2, sb, never); keep(w2, sb, never);
        TSTAMP(11);
    }
}

typedef CUresult (*EncodeFn)(CUtensorMap*, CUtensorMapDataType, cuuint32_t, void*, const cuuint64_t*, const cuuint64_t*,
                             const cuuint32_t*, const cuuint32_t*, CUtensorMapInterleave, CUtensorMapSwizzle,
                             CUtensorMapL2promotion, CUtensorMapFloatOOBfill);

void make_map(EncodeFn enc, CUtensorMap* tm, void* ptr, uint64_t cols, uint64_t rows, uint32_t box_cols, uint32_t box_rows,
              CUtensorMapSwizzle swz) {
    const cuuint64_t dims[2] = {cols, rows};
    const cuuint64_t strides[1] = {cols * 2};
    const cuuint32_t box[2] = {box_cols, box_rows};
    const cuuint32_t es[2] = {1, 1};
    enc(tm, CU_TENSOR_MAP_DATA_TYPE_BFLOAT16, 2, ptr, dims, strides, box, es, CU_TENSOR_MAP_INTERLEAVE_NONE, swz,
        CU_TENSOR_MAP_L2_PROMOTION_NONE, CU_TENSOR_MAP_FLOAT_OOB_FILL_NONE);
}

}

extern "C" void kernel_launch(void* const* d_in, const int* in_sizes, int n_in, void* d_out, int out_size) {
    (void)in_sizes; (void)n_in; (void)out_size;
    static EncodeFn enc = nullptr;
    if (!enc) {
        void* fn = nullptr;
        cudaDriverEntryPointQueryResult qr;
        cudaGetDriverEntryPoint("cuTensorMapEncodeTiled", &fn, cudaEnableDefault, &qr);
        enc = (EncodeFn)fn;
        cudaFuncSetAttribute(decode_block_kernel, cudaFuncAttributeMaxDynamicSharedMemorySize, SMEM_BYTES);
    }
    Maps tm;
    make_map(enc, &tm.v, d_in[2], 64, (uint64_t)2 * NHEAD * SK * 2, 64, TILE_KEYS * 2, CU_TENSOR_MAP_SWIZZLE_128B);
    make_map(enc, &tm.wq, d_in[3], QCOLS, D_MODEL, 64, 128, CU_TENSOR_MAP_SWIZZLE_128B);
    make_map(enc, &tm.wo, d_in[4], D_MODEL, QCOLS, 64, 128, CU_TENSOR_MAP_SWIZZLE_128B);
    make_map(enc, &tm.w1, d_in[6], FF, D_MODEL, 32, 256, CU_TENSOR_MAP_SWIZZLE_64B);
    make_map(enc, &tm.w2, d_in[8], D_MODEL, FF, 64, 32, CU_TENSOR_MAP_SWIZZLE_128B);
    decode_block_kernel<<<NCTA, NTHREADS, SMEM_BYTES>>>(
        tm, (const __nv_bfloat16*)d_in[0], (const __nv_bfloat16*)d_in[1], (const __nv_bfloat16*)d_in[7],
        (const __nv_bfloat16*)d_in[9], (__nv_bfloat16*)d_out);
}
```

```cpp
#include <cuda_runtime.h>
#include <cuda_bf16.h>
#include <cuda.h>
#include <stdint.h>

namespace {

constexpr int D_MODEL = 512;
constexpr int NHEAD = 32;
constexpr int SK = 8192;
constexpr int DH = 128;
constexpr int FF = 1376;
constexpr int QCOLS = NHEAD * DH;

constexpr int NCTA = 128;
constexpr int KEYS_PER_CTA = SK / 2;
constexpr int TILE_KEYS = 64;
constexpr int TILE_BYTES = TILE_KEYS * DH * 2;
constexpr int NTILE = KEYS_PER_CTA / TILE_KEYS;
#define NST_ 10
#define NINIT_ 4
#define WLATE_ 1
#define WTH_ 40
#define DLY1_ 150
#define DLY2_ 400
constexpr int NST = NST_;
constexpr int NINIT = NINIT_;
constexpr int WLATE = WLATE_;
constexpr int WTH = WTH_;
constexpr int DELAY1 = DLY1_, DELAY2 = DLY2_;
constexpr int NCONS = 256;
constexpr int NTHREADS = NCONS + 64;
constexpr int NMLP = FF / 32;
constexpr int KPRE = NST - 4;
constexpr int T_WQ = 0, T_K0 = 4, T_WO = T_K0 + KPRE, T_K1 = T_WO + 4, T_V = T_K1 + NTILE - KPRE, T_W1 = T_V + NTILE,
              T_W2 = T_W1 + 2, T_END = T_W2 + 2;

constexpr int OFF_RING = 0;
constexpr int OFF_SP = OFF_RING + NST * TILE_BYTES;
constexpr int OFF_PART = OFF_SP + KEYS_PER_CTA * 2;
constexpr int OFF_CS = OFF_PART + 8 * 64 * 4;
constexpr int OFF_XN = OFF_CS + 8 * 64 * 4;
constexpr int OFF_X = OFF_XN + 1024;
constexpr int O_STRIDE = 272;
constexpr int OFF_O = OFF_X + 2048 + 1024 + 64;
constexpr int OFF_Q = OFF_O + 4 * O_STRIDE;
constexpr int OFF_RED = OFF_Q + 256;
constexpr int OFF_STAT = OFF_RED + 64;
constexpr int OFF_HID = OFF_STAT + 128;
constexpr int OFF_ML = OFF_HID + 160;
constexpr int OFF_BAR = OFF_ML + 16;
constexpr int SMEM_USED = OFF_BAR + (2 * NST + 3) * 8;
constexpr int SMEM_BYTES = SMEM_USED + 1024;

constexpr float FX_SCALE = 1073741824.0f;
constexpr float FX_INV = 1.0f / 1073741824.0f;

constexpr int NFIN = 32;
struct Scratch {
    unsigned long long acc1[2 * D_MODEL];
    unsigned int ticket[8 * 32];
    uint4 part[NFIN * NMLP * 8];
};
__device__ __align__(1024) Scratch g_scratch;

#define TSTAMP(i)

__device__ __forceinline__ void mbar_init(uint32_t bar, uint32_t cnt) {
    asm volatile("mbarrier.init.shared::cta.b64 [%0], %1;" ::"r"(bar), "r"(cnt) : "memory");
}
__device__ __forceinline__ void mbar_expect_tx(uint32_t bar, uint32_t bytes) {
    asm volatile("mbarrier.arrive.expect_tx.shared::cta.b64 _, [%0], %1;" ::"r"(bar), "r"(bytes) : "memory");
}
__device__ __forceinline__ void mbar_arrive(uint32_t bar) {
    asm volatile("mbarrier.arrive.shared::cta.b64 _, [%0];" ::"r"(bar) : "memory");
}
__device__ __forceinline__ bool mbar_try(uint32_t bar, uint32_t parity) {
    uint32_t ok;
    asm volatile("{\n.reg .pred p;\nmbarrier.try_wait.parity.shared::cta.b64 p, [%1], %2;\nselp.u32 %0, 1, 0, p;\n}"
                 : "=r"(ok) : "r"(bar), "r"(parity) : "memory");
    return ok;
}
constexpr int SPIN_LIMIT = 1 << 20;
__device__ __forceinline__ void mbar_wait(uint32_t bar, uint32_t parity) {
    int n = 0;
    while (!mbar_try(bar, parity)) { if (++n > SPIN_LIMIT) __trap(); }
}
__device__ __forceinline__ void bulk_load(uint32_t dst, const void* src, uint32_t bytes, uint32_t bar) {
    asm volatile("cp.async.bulk.shared::cluster.global.mbarrier::complete_tx::bytes [%0], [%1], %2, [%3];"
                 ::"r"(dst), "l"(src), "r"(bytes), "r"(bar) : "memory");
}
__device__ __forceinline__ void tma2d(uint32_t dst, const CUtensorMap* tm, int c0, int c1, uint32_t bar) {
    asm volatile("cp.async.bulk.tensor.2d.shared::cluster.global.mbarrier::complete_tx::bytes [%0], [%1, {%3, %4}], [%2];"
                 ::"r"(dst), "l"(tm), "r"(bar), "r"(c0), "r"(c1) : "memory");
}
__device__ __forceinline__ void bulk_load_stream(uint32_t dst, const void* src, uint32_t bytes, uint32_t bar, uint64_t pol) {
    asm volatile("cp.async.bulk.shared::cluster.global.mbarrier::complete_tx::bytes.L2::cache_hint [%0], [%1], %2, [%3], %4;"
                 ::"r"(dst), "l"(src), "r"(bytes), "r"(bar), "l"(pol) : "memory");
}
__device__ __forceinline__ void tma2d_stream(uint32_t dst, const CUtensorMap* tm, int c0, int c1, uint32_t bar, uint64_t pol) {
    asm volatile("cp.async.bulk.tensor.2d.shared::cluster.global.mbarrier::complete_tx::bytes.L2::cache_hint [%0], [%1, {%3, %4}], [%2], %5;"
                 ::"r"(dst), "l"(tm), "r"(bar), "r"(c0), "r"(c1), "l"(pol) : "memory");
}
__device__ __forceinline__ bool elect_one() {
    uint32_t p;
    asm volatile("{\n.reg .pred p;\nelect.sync _|p, 0xffffffff;\nselp.u32 %0, 1, 0, p;\n}" : "=r"(p));
    return p;
}
__device__ __forceinline__ void cons_sync() { asm volatile("bar.sync 1, 256;" ::: "memory"); }

__device__ __forceinline__ uint32_t mapa(uint32_t addr, uint32_t rank) {
    uint32_t r;
    asm("mapa.shared::cluster.u32 %0, %1, %2;" : "=r"(r) : "r"(addr), "r"(rank));
    return r;
}
__device__ __forceinline__ void st_async_b32(uint32_t addr, uint32_t v, uint32_t bar) {
    asm volatile("st.async.weak.shared::cluster.mbarrier::complete_tx::bytes.b32 [%0], %1, [%2];" ::"r"(addr), "r"(v), "r"(bar) : "memory");
}
__device__ __forceinline__ void st_async_v2(uint32_t addr, uint32_t v0, uint32_t v1, uint32_t bar) {
    asm volatile("st.async.weak.shared::cluster.mbarrier::complete_tx::bytes.v2.b32 [%0], {%1, %2}, [%3];" ::"r"(addr), "r"(v0), "r"(v1), "r"(bar) : "memory");
}

__device__ __forceinline__ void mma_bf16(float (&d)[4], uint32_t a0, uint32_t a1, uint32_t a2, uint32_t a3, uint32_t b0, uint32_t b1) {
    asm volatile("mma.sync.aligned.m16n8k16.row.col.f32.bf16.bf16.f32 {%0,%1,%2,%3}, {%4,%5,%6,%7}, {%8,%9}, {%0,%1,%2,%3};"
                 : "+f"(d[0]), "+f"(d[1]), "+f"(d[2]), "+f"(d[3])
                 : "r"(a0), "r"(a1), "r"(a2), "r"(a3), "r"(b0), "r"(b1));
}
__device__ __forceinline__ void ldsm4(uint32_t (&r)[4], uint32_t addr) {
    asm volatile("ldmatrix.sync.aligned.m8n8.x4.shared.b16 {%0,%1,%2,%3}, [%4];"
                 : "=r"(r[0]), "=r"(r[1]), "=r"(r[2]), "=r"(r[3]) : "r"(addr) : "memory");
}
__device__ __forceinline__ void ldsm4t(uint32_t (&r)[4], uint32_t addr) {
    asm volatile("ldmatrix.sync.aligned.m8n8.x4.trans.shared.b16 {%0,%1,%2,%3}, [%4];"
                 : "=r"(r[0]), "=r"(r[1]), "=r"(r[2]), "=r"(r[3]) : "r"(addr) : "memory");
}
__device__ __forceinline__ uint4 lds128(uint32_t a) {
    uint4 v;
    asm volatile("ld.shared.v4.u32 {%0,%1,%2,%3}, [%4];" : "=r"(v.x), "=r"(v.y), "=r"(v.z), "=r"(v.w) : "r"(a) : "memory");
    return v;
}
__device__ __forceinline__ uint2 lds64(uint32_t a) {
    uint2 v;
    asm volatile("ld.shared.v2.u32 {%0,%1}, [%2];" : "=r"(v.x), "=r"(v.y) : "r"(a) : "memory");
    return v;
}
__device__ __forceinline__ uint32_t lds32(uint32_t a) {
    uint32_t v;
    asm volatile("ld.shared.u32 %0, [%1];" : "=r"(v) : "r"(a) : "memory");
    return v;
}
__device__ __forceinline__ void sts128(uint32_t a, uint4 v) {
    asm volatile("st.shared.v4.u32 [%0], {%1,%2,%3,%4};" ::"r"(a), "r"(v.x), "r"(v.y), "r"(v.z), "r"(v.w) : "memory");
}
__device__ __forceinline__ void sts64(uint32_t a, uint32_t v0, uint32_t v1) {
    asm volatile("st.shared.v2.u32 [%0], {%1,%2};" ::"r"(a), "r"(v0), "r"(v1) : "memory");
}
__device__ __forceinline__ void sts32(uint32_t a, uint32_t v) {
    asm volatile("st.shared.u32 [%0], %1;" ::"r"(a), "r"(v) : "memory");
}
__device__ __forceinline__ void sts16(uint32_t a, uint16_t v) {
    asm volatile("st.shared.u16 [%0], %1;" ::"r"(a), "h"(v) : "memory");
}
__device__ __forceinline__ float bf_lo(uint32_t v) { return __uint_as_float(v << 16); }
__device__ __forceinline__ float bf_hi(uint32_t v) { return __uint_as_float(v & 0xffff0000u); }
__device__ __forceinline__ uint32_t pack_bf(float lo, float hi) {
    uint32_t r;
    asm("cvt.rn.bf16x2.f32 %0, %1, %2;" : "=r"(r) : "f"(hi), "f"(lo));
    return r;
}
__device__ __forceinline__ float rnd_bf(float v) { return bf_lo(pack_bf(v, 0.f)); }

__device__ __forceinline__ unsigned long long fx_encode(float v) {
    return ((unsigned long long)__float2ll_rn(v * FX_SCALE) << 8) + 1ull;
}
__device__ __forceinline__ float fx_decode(uint32_t lo, uint32_t hi) {
    return fmaf(__int2float_rn((int)hi), 1.0f / 64.0f, __uint2float_rn(lo & 0xffffff00u) * (FX_INV / 256.0f));
}
__device__ __forceinline__ void spin_cycles(uint32_t n) {
    uint32_t t0, t;
    asm volatile("mov.u32 %0, %%clock;" : "=r"(t0));
    do { asm volatile("mov.u32 %0, %%clock;" : "=r"(t)); } while (t - t0 < n);
}
__device__ __forceinline__ void red_add64(unsigned long long* p, unsigned long long v) {
    asm volatile("red.relaxed.gpu.global.add.u64 [%0], %1;" ::"l"(p), "l"(v) : "memory");
}
__device__ __forceinline__ void ld_relaxed2x64(uint4& v, const void* p) {
    asm volatile("{\n.reg .b64 a, b;\nld.relaxed.gpu.global.v2.b64 {a, b}, [%4];\nmov.b64 {%0, %1}, a;\nmov.b64 {%2, %3}, b;\n}"
                 : "=r"(v.x), "=r"(v.y), "=r"(v.z), "=r"(v.w) : "l"(p) : "memory");
}
__device__ __forceinline__ void ld_relaxed128(uint4& v, const uint4* p) {
    asm volatile("ld.relaxed.gpu.global.v4.u32 {%0,%1,%2,%3}, [%4];" : "=r"(v.x), "=r"(v.y), "=r"(v.z), "=r"(v.w) : "l"(p) : "memory");
}
__device__ __forceinline__ uint32_t and3(uint32_t a, uint32_t b, uint32_t c) {
    uint32_t r;
    asm("lop3.b32 %0, %1, %2, %3, 0x80;" : "=r"(r) : "r"(a), "r"(b), "r"(c));
    return r;
}
__device__ __forceinline__ bool all_marked(const uint4& a, const uint4& b) {
    return __all_sync(~0u, and3(and3(a.x, a.y, a.z), and3(a.w, b.x, b.y), and3(b.z, b.w, 1u)));
}
__device__ __forceinline__ bool all_complete(const uint4& a, const uint4& b) {
    return __all_sync(~0u, and3(and3(a.x, a.z, b.x), b.z, 32u));
}
__device__ __forceinline__ float bf16_at(uint32_t a) {
    uint16_t v;
    asm volatile("ld.shared.u16 %0, [%1];" : "=h"(v) : "r"(a) : "memory");
    return __uint_as_float((uint32_t)v << 16);
}
__device__ __forceinline__ unsigned ld_relaxed32(const unsigned* p) {
    unsigned v;
    asm volatile("ld.relaxed.gpu.global.u32 %0, [%1];" : "=r"(v) : "l"(p) : "memory");
    return v;
}

__device__ __forceinline__ int bpos(int k) { return ((k >> 1) & 3) * 16 + ((k >> 4) & 3) * 4 + ((k >> 3) & 1) * 2 + (k & 1); }

__device__ __forceinline__ void gemv1_partial(const uint32_t* a1, uint32_t hb0, uint32_t hb1, int j, int c, uint32_t a) {
    float t0[4] = {0.f, 0.f, 0.f, 0.f}, t1[4] = {0.f, 0.f, 0.f, 0.f}, t2[4] = {0.f, 0.f, 0.f, 0.f}, t3[4] = {0.f, 0.f, 0.f, 0.f};
#pragma unroll
    for (int k = 0; k < 2; k++) {
        const uint32_t m0 = (j == k) ? hb0 : 0u, m1 = (j == k) ? hb1 : 0u;
        const uint32_t n0 = (j == k + 2) ? hb0 : 0u, n1 = (j == k + 2) ? hb1 : 0u;
        mma_bf16(t0, a1[8 * k], a1[8 * k + 1], a1[8 * k + 2], a1[8 * k + 3], m0, m1);
        mma_bf16(t1, a1[8 * k + 4], a1[8 * k + 5], a1[8 * k + 6], a1[8 * k + 7], m0, m1);
        mma_bf16(t2, a1[8 * k + 16], a1[8 * k + 17], a1[8 * k + 18], a1[8 * k + 19], n0, n1);
        mma_bf16(t3, a1[8 * k + 20], a1[8 * k + 21], a1[8 * k + 22], a1[8 * k + 23], n0, n1);
    }
    const bool up2 = c & 2, up1 = c & 1;
    float r4[4], r2[2];
    const float send[4] = {up2 ? t2[0] : t0[1], up2 ? t2[2] : t0[3], up2 ? t3[0] : t1[1], up2 ? t3[2] : t1[3]};
    const float keep[4] = {up2 ? t2[1] : t0[0], up2 ? t2[3] : t0[2], up2 ? t3[1] : t1[0], up2 ? t3[3] : t1[2]};
#pragma unroll
    for (int i = 0; i < 4; i++) r4[i] = keep[i] + __shfl_xor_sync(~0u, send[i], 2);
#pragma unroll
    for (int i = 0; i < 2; i++) r2[i] = (up1 ? r4[i + 2] : r4[i]) + __shfl_xor_sync(~0u, up1 ? r4[i] : r4[i + 2], 1);
    sts32(a, __float_as_uint(r2[0]));
    sts32(a + 32, __float_as_uint(r2[1]));
}

__device__ __forceinline__ float sum8(uint32_t a) {
    float p[8];
#pragma unroll
    for (int w = 0; w < 8; w++) p[w] = __uint_as_float(lds32(a + w * 256));
    return ((p[0] + p[1]) + (p[2] + p[3])) + ((p[4] + p[5]) + (p[6] + p[7]));
}

struct Maps { CUtensorMap v, wq, wo, w1, w2; };

__global__ void __cluster_dims__(2, 1, 1) __launch_bounds__(NTHREADS, 1)
decode_block_kernel(const __grid_constant__ Maps tm,
                    const __nv_bfloat16* __restrict__ x, const __nv_bfloat16* __restrict__ Kc,
                    const __nv_bfloat16* __restrict__ b1, const __nv_bfloat16* __restrict__ b2,
                    __nv_bfloat16* __restrict__ out, Scratch* __restrict__ scr) {
    unsigned long long* const g_acc1 = scr->acc1;
    unsigned int* const g_ticket = scr->ticket;
    uint4* const g_part = scr->part;
    extern __shared__ unsigned char smem_raw[];
    const uint32_t sb = ((uint32_t)__cvta_generic_to_shared(smem_raw) + 1023u) & ~1023u;
    const uint32_t bar_full = sb + OFF_BAR, bar_empty = bar_full + NST * 8;
    const uint32_t bar_q = bar_empty + NST * 8, bar_ml = bar_q + 8, bar_o = bar_ml + 8;

    TSTAMP(0);
    int tid = threadIdx.x;
    asm volatile("" : "+r"(tid));
    const int lane = tid & 31;
    const int warp = __shfl_sync(~0u, tid >> 5, 0);
    const int bh = blockIdx.x >> 1, rank = blockIdx.x & 1;
    const int b = bh >> 5, h = bh & 31;
    const bool is_mlp = (rank == 0) && (bh < NMLP);
    const int f0 = bh * 32;

    const char* ksrc = (const char*)Kc + (size_t)blockIdx.x * (KEYS_PER_CTA * DH * 2);
    constexpr uint64_t pol = 0x12F0000000000000ull;
    if (elect_one()) {
        if (warp < 6) {
            const int s = warp < 2 ? T_K0 + warp : warp - 2;
            const uint32_t fb = bar_full + s * 8;
            mbar_init(fb, 1);
            asm volatile("fence.mbarrier_init.release.cluster;" ::: "memory");
            mbar_expect_tx(fb, TILE_BYTES);
            if (warp < 2) bulk_load_stream(sb + OFF_RING + s * TILE_BYTES, ksrc + (size_t)warp * TILE_BYTES, TILE_BYTES, fb, pol);
            else tma2d(sb + OFF_RING + s * TILE_BYTES, &tm.wq, h * DH + rank * 64, s * 128, fb);
        } else if (warp == 7) {
#pragma unroll
            for (int s = 0; s < NST; s++) mbar_init(bar_empty + s * 8, 8);
            asm volatile("fence.mbarrier_init.release.cluster;" ::: "memory");
        } else if (warp == 8) {
#pragma unroll
            for (int s = T_K0 + 2; s < NST; s++) mbar_init(bar_full + s * 8, 1);
            asm volatile("fence.mbarrier_init.release.cluster;" ::: "memory");
#pragma unroll
            for (int s = T_K0 + 2; s < T_K0 + NINIT; s++) {
                mbar_expect_tx(bar_full + s * 8, TILE_BYTES);
                bulk_load_stream(sb + OFF_RING + s * TILE_BYTES, ksrc + (size_t)(s - T_K0) * TILE_BYTES, TILE_BYTES, bar_full + s * 8, pol);
            }
        } else if (warp == 9) {
            mbar_init(bar_q, 2); mbar_init(bar_ml, 1); mbar_init(bar_o, 10);
            asm volatile("fence.mbarrier_init.release.cluster;" ::: "memory");
            mbar_expect_tx(bar_q, 128);
            mbar_expect_tx(bar_ml, is_mlp ? 8 + 2048 + 1024 + 64 : 8);
            if (is_mlp) {
                bulk_load(sb + OFF_X, x, 2048, bar_ml);
                bulk_load(sb + OFF_X + 2048, b2, 1024, bar_ml);
                bulk_load(sb + OFF_X + 3072, b1 + f0, 64, bar_ml);
            }
            mbar_expect_tx(bar_o, 512);
            asm volatile("prefetch.tensormap [%0];" ::"l"(&tm.wo) : "memory");
            asm volatile("prefetch.tensormap [%0];" ::"l"(&tm.v) : "memory");
            asm volatile("prefetch.tensormap [%0];" ::"l"(&tm.w1) : "memory");
            asm volatile("prefetch.tensormap [%0];" ::"l"(&tm.w2) : "memory");
        }
    }
    __syncwarp();
    asm volatile("barrier.cluster.arrive.relaxed.aligned;" ::: "memory");

    if (warp == 8) {
        asm volatile("barrier.cluster.wait.aligned;" ::: "memory");
        if (lane == 0) {
#pragma unroll
            for (int w = 0; w < 4; w++) mbar_wait(bar_full + (T_WQ + w) * 8, 0);
#pragma unroll
            for (int k = NINIT; k < KPRE; k++) {
                const uint32_t fb = bar_full + (T_K0 + k) * 8;
                mbar_expect_tx(fb, TILE_BYTES);
                bulk_load_stream(sb + OFF_RING + (T_K0 + k) * TILE_BYTES, ksrc + (size_t)k * TILE_BYTES, TILE_BYTES, fb, pol);
            }
            const int vline0 = (bh * SK + rank * KEYS_PER_CTA) * 2;
            const int tend = is_mlp ? T_END : T_W1;
            int st = 0, ph = 0;
#pragma unroll 1
            for (int t = NST; t < tend; t++) {
                const uint32_t dst = sb + OFF_RING + st * TILE_BYTES, fb = bar_full + st * 8;
                mbar_wait(bar_empty + st * 8, ph);
                if (t == T_W1) {
                    mbar_wait(bar_full + ((T_W1 - 1 - WLATE) % NST) * 8, ((T_W1 - 1 - WLATE) / NST) & 1);
                    int n = 0;
                    while (ld_relaxed32(g_ticket) < (unsigned)WTH) { __nanosleep(100); if (++n > SPIN_LIMIT) __trap(); }
                }
                mbar_expect_tx(fb, TILE_BYTES);
                if (t < T_K1) {
                    tma2d(dst, &tm.wo, rank * 256 + (t - T_WO) * 64, h * DH, fb);
                } else if (t < T_V) {
                    bulk_load_stream(dst, ksrc + (size_t)(t - 8) * TILE_BYTES, TILE_BYTES, fb, pol);
                } else if (t < T_W1) {
                    tma2d_stream(dst, &tm.v, 0, vline0 + (t - T_V) * (TILE_KEYS * 2), fb, pol);
                } else if (t < T_W2) {
                    tma2d(dst, &tm.w1, f0, (t - T_W1) * 256, fb);
                } else {
#pragma unroll
                    for (int i = 0; i < 4; i++) tma2d(dst + i * 4096, &tm.w2, ((t - T_W2) * 4 + i) * 64, f0, fb);
                }
                if (++st == NST) { st = 0; ph ^= 1; }
            }
        }
        return;
    }

    if (warp == 9) {
        if (is_mlp) {
#pragma unroll
            for (int i = 0; i < 8; i++) g_part[((i * 4 + (lane >> 3)) * NMLP + bh) * 8 + (lane & 7)] = make_uint4(0, 0, 0, 0);
            __threadfence();
        }
        asm volatile("barrier.cluster.wait.aligned;" ::: "memory");
        if (lane == 0) mbar_arrive(bar_o);
        return;
    }

    const int g = lane >> 2, c = lane & 3;
    const int rr = lane & 7, mi = lane >> 3;
    const int mb_ = g & 1, j4 = g >> 1;
    const int d0 = warp * 64 + j4 * 16 + c * 2;
    uint32_t qa[16], wf[64];
    {
        if (warp == 6) {
            const uint4 xa0 = __ldg((const uint4*)(x + b * D_MODEL) + lane), xa1 = __ldg((const uint4*)(x + b * D_MODEL) + 32 + lane);
            const uint32_t xa[8] = {xa0.x, xa0.y, xa0.z, xa0.w, xa1.x, xa1.y, xa1.z, xa1.w};
            float s = 0.f;
#pragma unroll
            for (int i = 0; i < 8; i++) s += bf_lo(xa[i]) + bf_hi(xa[i]);
#pragma unroll
            for (int o = 16; o; o >>= 1) s += __shfl_xor_sync(~0u, s, o);
            const float mean = s * (1.0f / D_MODEL);
            float v = 0.f;
#pragma unroll
            for (int i = 0; i < 8; i++) { const float e0 = bf_lo(xa[i]) - mean, e1 = bf_hi(xa[i]) - mean; v += e0 * e0 + e1 * e1; }
#pragma unroll
            for (int o = 16; o; o >>= 1) v += __shfl_xor_sync(~0u, v, o);
            const float mb = rnd_bf(mean);
            const float den = rnd_bf(sqrtf(rnd_bf(rnd_bf(v * (1.0f / D_MODEL)) + 1e-5f)));
#pragma unroll
            for (int i = 0; i < 8; i++) {
                const int k = (i >> 2) * 256 + lane * 8 + (i & 3) * 2;
                sts32(sb + OFF_XN + ((k & ~63) + bpos(k)) * 2,
                      pack_bf(__fdiv_rn(rnd_bf(bf_lo(xa[i]) - mb), den), __fdiv_rn(rnd_bf(bf_hi(xa[i]) - mb), den)));
            }
        }
        asm volatile("barrier.cluster.wait.aligned;" ::: "memory");
        TSTAMP(12);
        cons_sync();

        float q0[4] = {0.f, 0.f, 0.f, 0.f}, q1[4] = {0.f, 0.f, 0.f, 0.f};
        const uint32_t aoff = ((warp >> 2) * 64 + (mi >> 1) * 8 + rr) * 128 + (((warp & 3) * 2 + (mi & 1)) ^ rr) * 16;
#pragma unroll
        for (int t = 0; t < 4; t++) {
            const uint32_t xaddr = sb + OFF_XN + (t * 2 + (warp >> 2)) * 128 + c * 32;
            const uint4 p0 = lds128(xaddr), p1 = lds128(xaddr + 16);
            const uint32_t base = sb + OFF_RING + (T_WQ + t) * TILE_BYTES + aoff;
            mbar_wait(bar_full + (T_WQ + t) * 8, 0);
            uint32_t a0[4], a1[4], a2[4], a3[4];
            ldsm4t(a0, base); ldsm4t(a1, base + 2048); ldsm4t(a2, base + 4096); ldsm4t(a3, base + 6144);
            mma_bf16(q0, a0[0], a0[1], a0[2], a0[3], p0.x, p0.y);
            mma_bf16(q1, a1[0], a1[1], a1[2], a1[3], p0.z, p0.w);
            mma_bf16(q0, a2[0], a2[1], a2[2], a2[3], p1.x, p1.y);
            mma_bf16(q1, a3[0], a3[1], a3[2], a3[3], p1.z, p1.w);
            __syncwarp();
            if (lane == 0) mbar_arrive(bar_empty + (T_WQ + t) * 8);
        }
        TSTAMP(13);
        if (c < 2) sts32(sb + OFF_PART + (warp * 16 + c * 8 + g) * 4, __float_as_uint(c ? q0[2] + q1[2] : q0[0] + q1[0]));
        cons_sync();
        if (warp == 0) {
            const uint2 u = lds64(sb + OFF_PART + lane * 8), w = lds64(sb + OFF_PART + 256 + lane * 8);
            const uint32_t qq = pack_bf(__uint_as_float(u.x) + __uint_as_float(w.x), __uint_as_float(u.y) + __uint_as_float(w.y));
            const uint32_t dst = sb + OFF_Q + rank * 128 + lane * 4;
            sts32(dst, qq);
            st_async_b32(mapa(dst, rank ^ 1), qq, mapa(bar_q, rank ^ 1));
            __syncwarp();
            if (lane == 0) mbar_arrive(bar_q);
        }
        mbar_wait(bar_q, 0);
#pragma unroll
        for (int j = 0; j < 16; j++) qa[j] = lds32(sb + OFF_Q + ((j & 8) + ((g + j) & 7)) * 16 + c * 4);
    }
    TSTAMP(1);

    int st = T_K0, ph = 0;
    float mx = -INFINITY;
    {
        uint32_t koff0 = sb + OFF_RING + (warp * 8 + rr) * 256 + ((rr + mi) & 7) * 16;
        uint32_t koff1 = sb + OFF_RING + (warp * 8 + rr) * 256 + ((rr + mi + 4) & 7) * 16;
        asm volatile("" : "+r"(koff0), "+r"(koff1));
        const bool valid = (c == (g >> 1));
        uint32_t spos = sb + OFF_SP + bpos(warp * 8 + g) * 2;
        auto k_tiles = [&](int n) {
#pragma unroll 1
            for (int i = 0; i < n; i++) {
                const uint32_t base = st * TILE_BYTES;
                mbar_wait(bar_full + st * 8, ph);
                uint32_t k0[4], k1[4], k2[4], k3[4];
                ldsm4(k0, base + koff0); ldsm4(k1, base + koff1);
                ldsm4(k2, base + koff0 + 128); ldsm4(k3, base + koff1 + 128);
                float s0[4] = {0.f, 0.f, 0.f, 0.f}, s1[4] = {0.f, 0.f, 0.f, 0.f};
                mma_bf16(s0, qa[0], qa[2], qa[1], qa[3], k0[0], k0[1]);
                mma_bf16(s1, qa[0], qa[2], qa[1], qa[3], k0[2], k0[3]);
                mma_bf16(s0, qa[4], qa[6], qa[5], qa[7], k1[0], k1[1]);
                mma_bf16(s1, qa[4], qa[6], qa[5], qa[7], k1[2], k1[3]);
                mma_bf16(s0, qa[8], qa[10], qa[9], qa[11], k2[0], k2[1]);
                mma_bf16(s1, qa[8], qa[10], qa[9], qa[11], k2[2], k2[3]);
                mma_bf16(s0, qa[12], qa[14], qa[13], qa[15], k3[0], k3[1]);
                mma_bf16(s1, qa[12], qa[14], qa[13], qa[15], k3[2], k3[3]);
                __syncwarp();
                if (lane == 0) mbar_arrive(bar_empty + st * 8);
                const float raw = (g & 1) ? s0[1] + s1[3] : s0[0] + s1[2];
                const uint32_t sc = pack_bf(rnd_bf(raw) * 0.08838834764831845f, 0.f);
                if (valid) { sts16(spos, (uint16_t)sc); mx = fmaxf(mx, bf_lo(sc)); }
                spos += TILE_KEYS * 2;
                if (++st == NST) { st = 0; ph ^= 1; }
            }
        };
        k_tiles(KPRE);
        {
            static_assert(T_WO == NST, "wo tiles sit in slots 0..3, second pass");
            const int s = warp >> 1;
            const int row = (mi >> 1) * 4 + (rr >> 1) + (rr & 1) * 8;
            const uint32_t base = sb + OFF_RING + s * TILE_BYTES + row * 128;
            const uint32_t c0 = (((mi & 1) * 2 + (warp & 1)) ^ (row & 7)) * 16, c1 = c0 ^ 64;
            mbar_wait(bar_full + s * 8, 1);
#pragma unroll
            for (int t = 0; t < 8; t++) {
                ldsm4t(*(uint32_t(*)[4])(wf + 8 * t), base + t * 2048 + c0);
                ldsm4t(*(uint32_t(*)[4])(wf + 8 * t + 4), base + t * 2048 + c1);
            }
            __syncwarp();
            if (lane < 4) mbar_arrive(bar_empty + lane * 8);
            st = 4;
        }
        k_tiles(NTILE - KPRE);
    }
    TSTAMP(2);
    {
#pragma unroll
        for (int o = 16; o; o >>= 1) mx = fmaxf(mx, __shfl_xor_sync(~0u, mx, o));
        if (lane == 0) sts32(sb + OFF_RED + warp * 4, __float_as_uint(mx));
        cons_sync();
        const uint4 m0 = lds128(sb + OFF_RED), m1 = lds128(sb + OFF_RED + 16);
        const float mloc = fmaxf(fmaxf(fmaxf(__uint_as_float(m0.x), __uint_as_float(m0.y)), fmaxf(__uint_as_float(m0.z), __uint_as_float(m0.w))),
                                 fmaxf(fmaxf(__uint_as_float(m1.x), __uint_as_float(m1.y)), fmaxf(__uint_as_float(m1.z), __uint_as_float(m1.w))));
        const uint4 s0 = lds128(sb + OFF_SP + tid * 16), s1 = lds128(sb + OFF_SP + 4096 + tid * 16);
        const uint32_t sv[8] = {s0.x, s0.y, s0.z, s0.w, s1.x, s1.y, s1.z, s1.w};
        constexpr float LOG2E = 1.4426950408889634f;
        float l = 0.f;
#pragma unroll
        for (int i = 0; i < 8; i++) l += exp2f((bf_lo(sv[i]) - mloc) * LOG2E) + exp2f((bf_hi(sv[i]) - mloc) * LOG2E);
#pragma unroll
        for (int o = 16; o; o >>= 1) l += __shfl_xor_sync(~0u, l, o);
        if (lane == 0) sts32(sb + OFF_RED + 32 + warp * 4, __float_as_uint(l));
        cons_sync();
        const uint4 l0 = lds128(sb + OFF_RED + 32), l1 = lds128(sb + OFF_RED + 48);
        const float lloc = ((__uint_as_float(l0.x) + __uint_as_float(l0.y)) + (__uint_as_float(l0.z) + __uint_as_float(l0.w))) +
                           ((__uint_as_float(l1.x) + __uint_as_float(l1.y)) + (__uint_as_float(l1.z) + __uint_as_float(l1.w)));
        if (tid == 0) st_async_v2(mapa(sb + OFF_ML, rank ^ 1), __float_as_uint(mloc), __float_as_uint(lloc), mapa(bar_ml, rank ^ 1));
        mbar_wait(bar_ml, 0);
        const uint2 pml = lds64(sb + OFF_ML);
        const float mp = __uint_as_float(pml.x), lp = __uint_as_float(pml.y);
        const float M = fmaxf(mloc, mp);
        const float m_a = rank ? mp : mloc, l_a = rank ? lp : lloc, m_b = rank ? mloc : mp, l_b = rank ? lloc : lp;
        const float L = l_a * exp2f((m_a - M) * LOG2E) + l_b * exp2f((m_b - M) * LOG2E);
        const float inv = 1.0f / L;
        uint32_t pv[8];
#pragma unroll
        for (int i = 0; i < 8; i++)
            pv[i] = pack_bf(exp2f((bf_lo(sv[i]) - M) * LOG2E) * inv, exp2f((bf_hi(sv[i]) - M) * LOG2E) * inv);
        sts128(sb + OFF_SP + tid * 16, make_uint4(pv[0], pv[1], pv[2], pv[3]));
        sts128(sb + OFF_SP + 4096 + tid * 16, make_uint4(pv[4], pv[5], pv[6], pv[7]));
        cons_sync();
    }
    TSTAMP(3);
    unsigned long long* acc1_dst = g_acc1 + b * D_MODEL + rank * 256 + warp * 32 + c * 8 + g;
    unsigned* ticket_dst = g_ticket + (tid & 7) * 32;
    uint32_t o_dst = sb + OFF_O + (rank * 2 + (c & 1)) * O_STRIDE + (warp * 8 + g) * 4, o_bar = bar_o;
    if (c & 2) { o_dst = mapa(o_dst, rank ^ 1); o_bar = mapa(bar_o, rank ^ 1); }
    uint32_t o_src = sb + OFF_O + (rr & 3) * O_STRIDE + mi * 16;
    asm volatile("" : "+l"(acc1_dst), "+l"(ticket_dst), "+r"(o_dst), "+r"(o_bar), "+r"(o_src));
    const bool is_fin = bh < NFIN;
    const unsigned* ticket_src = g_ticket + warp * 32;
    const unsigned long long* p1 = g_acc1 + mb_ * D_MODEL + warp * 64 + j4 * 8 + c * 2;
    uint4* part_dst = g_part + ((warp * 4 + c) * NMLP + bh) * 8 + g;
    const uint4* inbox = g_part + bh * (NMLP * 8) + tid;
    const uint4* inbox2 = tid < (NMLP - 32) * 8 ? inbox + 256 : inbox;
    const uint4* inbox_pf = g_part + (bh * NMLP + tid) * 8;
    int do_pf = is_fin && tid < NMLP;
    float wsel = tid < (NMLP - 32) * 8 ? 1.0f : 0.0f;
    __nv_bfloat16* out_dst = out + ((lane >> 3) & 1) * D_MODEL + bh * 16 + (lane >> 4) * 8 + (lane & 7);
    asm volatile("" : "+l"(ticket_src), "+l"(p1), "+l"(part_dst), "+l"(inbox), "+l"(inbox2), "+l"(inbox_pf), "+r"(do_pf), "+f"(wsel), "+l"(out_dst));
    uint32_t xv[2] = {lds32(sb + OFF_X + (mb_ * D_MODEL + d0) * 2), lds32(sb + OFF_X + (mb_ * D_MODEL + d0 + 8) * 2)};
    float b1v = bf16_at(sb + OFF_X + 3072 + lane * 2);
    float b2v = bf16_at(sb + OFF_X + 2048 + ((bh & 31) * 16 + (lane >> 4) * 8 + (lane & 7)) * 2);
    uint32_t a_part = sb + OFF_PART + warp * 256 + ((c >> 1) * 32 + (c & 1) * 16 + g) * 4;
    uint32_t a_stat = sb + OFF_STAT + (mb_ * 16 + (c & 1) * 8 + warp) * 4;
    uint32_t a_keep = sb + OFF_RED + mb_ * 32 + c * 4;
    uint32_t a_sum = sb + OFF_PART + (warp * 32 + lane) * 4, a_cs = sb + OFF_CS + lane * 4;
    uint32_t a_hid = sb + OFF_HID + warp * 80 + lane * 2, a_hidb = sb + OFF_HID + (rr & 1) * 80 + mi * 16;
    uint32_t a_fin = sb + OFF_PART + warp * 256 + lane * 4;
    uint32_t a_hfin = sb + OFF_RED + ((lane >> 3) & 1) * 32 + ((lane >> 4) * 8 + (lane & 7)) * 2;
    int keep_h = warp * 4 + j4 == bh;
    asm volatile("" : "+r"(a_part), "+r"(a_stat), "+r"(a_keep), "+r"(a_sum), "+r"(a_cs), "+r"(a_hid), "+r"(a_hidb), "+r"(a_fin), "+r"(a_hfin),
                 "+r"(keep_h), "+f"(b1v), "+f"(b2v));
    static_assert(T_W1 % NST + 3 < NST, "w1/w2 occupy four consecutive slots with the same parity");
    constexpr int W_PAR = (T_W1 / NST) & 1;
    uint32_t w1_bar = bar_full + (T_W1 % NST + (warp >> 2)) * 8;
    uint32_t w1_a = sb + OFF_RING + (T_W1 % NST + (warp >> 2)) * TILE_BYTES + ((warp & 3) * 64 + (mi >> 1) * 8 + rr) * 64 + ((mi & 1) ^ (rr >> 1)) * 16;
    uint32_t w2_a = sb + OFF_RING + (T_W2 % NST + (warp >> 2)) * TILE_BYTES + (warp & 3) * 4096 + ((mi >> 1) * 8 + rr) * 128 + ((mi & 1) ^ rr) * 16;
    asm volatile("" : "+r"(w1_bar), "+r"(w1_a), "+r"(w2_a));
    {
        const int hh = warp >> 2, ch = 2 * (warp & 3);
        const int line = 2 * (8 * (mi >> 1) + rr) + hh;
        uint32_t voff = sb + OFF_RING + line * 128 + (((ch ^ (mi & 1) ^ (rr >> 2)) ^ (line & 7)) * 16);
        uint32_t pmask = ((c >> 1) == (g & 1)) ? 0xffffffffu : 0u;
        asm volatile("" : "+r"(voff), "+r"(pmask));
        uint32_t paddr = sb + OFF_SP + c * 32;
        float o0[4] = {0.f, 0.f, 0.f, 0.f}, o1[4] = {0.f, 0.f, 0.f, 0.f};
#pragma unroll 1
        for (int i = 0; i < NTILE; i++) {
            const uint32_t base = voff + st * TILE_BYTES;
            uint4 p0 = lds128(paddr), p1 = lds128(paddr + 16);
            p0.x &= pmask; p0.y &= pmask; p0.z &= pmask; p0.w &= pmask;
            p1.x &= pmask; p1.y &= pmask; p1.z &= pmask; p1.w &= pmask;
            asm volatile("" : "+r"(p0.x), "+r"(p0.y), "+r"(p0.z), "+r"(p0.w), "+r"(p1.x), "+r"(p1.y), "+r"(p1.z), "+r"(p1.w));
            mbar_wait(bar_full + st * 8, ph);
            uint32_t a0[4], a1[4], a2[4], a3[4];
            ldsm4t(a0, base); ldsm4t(a1, base + 4096); ldsm4t(a2, base + 8192); ldsm4t(a3, base + 12288);
            if (i == NTILE - 1 && tid < 8) asm volatile("red.relaxed.gpu.global.add.u32 [%0], 1;" ::"l"(ticket_dst) : "memory");
            mma_bf16(o0, a0[0], a0[1], a0[2], a0[3], p0.x, p0.y);
            mma_bf16(o1, a1[0], a1[1], a1[2], a1[3], p0.z, p0.w);
            mma_bf16(o0, a2[0], a2[1], a2[2], a2[3], p1.x, p1.y);
            mma_bf16(o1, a3[0], a3[1], a3[2], a3[3], p1.z, p1.w);
            __syncwarp();
            if (lane == 0) mbar_arrive(bar_empty + st * 8);
            paddr += TILE_KEYS * 2;
            if (++st == NST) { st = 0; ph ^= 1; }
        }
        TSTAMP(4);
        const float v0 = (o0[0] + o1[0]) + (o0[3] + o1[3]);
        const float v1 = (o0[1] + o1[1]) + (o0[2] + o1[2]);
        const uint32_t hi = pack_bf(v0, v1);
        const uint32_t val = (c & 1) ? pack_bf(v0 - bf_lo(hi), v1 - bf_hi(hi)) : hi;
        if (c & 2) st_async_b32(o_dst, val, o_bar);
        else sts32(o_dst, val);
        __syncwarp();
        if (lane == 0) mbar_arrive(bar_o);
        mbar_wait(bar_o, 0);
    }
    TSTAMP(5);
    {
        float d00[4] = {0.f, 0.f, 0.f, 0.f}, d01[4] = {0.f, 0.f, 0.f, 0.f}, d10[4] = {0.f, 0.f, 0.f, 0.f}, d11[4] = {0.f, 0.f, 0.f, 0.f};
        uint32_t ob[4][4];
#pragma unroll
        for (int t = 0; t < 4; t++) ldsm4(ob[t], o_src + t * 64);
#pragma unroll
        for (int t = 0; t < 4; t++) {
            mma_bf16(d00, wf[16 * t], wf[16 * t + 1], wf[16 * t + 2], wf[16 * t + 3], ob[t][0], ob[t][1]);
            mma_bf16(d10, wf[16 * t + 4], wf[16 * t + 5], wf[16 * t + 6], wf[16 * t + 7], ob[t][0], ob[t][1]);
            mma_bf16(d01, wf[16 * t + 8], wf[16 * t + 9], wf[16 * t + 10], wf[16 * t + 11], ob[t][2], ob[t][3]);
            mma_bf16(d11, wf[16 * t + 12], wf[16 * t + 13], wf[16 * t + 14], wf[16 * t + 15], ob[t][2], ob[t][3]);
        }
        const float e0 = (d00[0] + d01[0]) + (d00[1] + d01[1]), e1 = (d00[2] + d01[2]) + (d00[3] + d01[3]);
        const float e2 = (d10[0] + d11[0]) + (d10[1] + d11[1]), e3 = (d10[2] + d11[2]) + (d10[3] + d11[3]);
        const float ea = (c & 2) ? e2 : e0, eb = (c & 2) ? e3 : e1;
        const float e = ((c & 1) ? eb : ea) + __shfl_xor_sync(~0u, (c & 1) ? ea : eb, 1);
        red_add64(acc1_dst, fx_encode(e));
    }
    TSTAMP(6);
    if (!is_mlp) return;

    {
        if (do_pf) asm volatile("prefetch.global.L2 [%0];" ::"l"(inbox_pf));
        uint32_t* a1 = wf;
        uint32_t* a2 = wf + 32;
        mbar_wait(w1_bar, W_PAR);
#pragma unroll
        for (int k = 0; k < 4; k++) {
            ldsm4t(*(uint32_t(*)[4])(a1 + 8 * k), w1_a + k * 1024);
            ldsm4t(*(uint32_t(*)[4])(a1 + 8 * k + 4), (w1_a ^ 32) + k * 1024);
        }
        gemv1_partial(a1, 0x3f803f80u, 0x3f803f80u, j4, c, a_part + (OFF_CS - OFF_PART));
        TSTAMP(7);
        uint32_t hb0, hb1;
        {
            uint4 ua, ub;
            ld_relaxed2x64(ua, p1); ld_relaxed2x64(ub, p1 + 32);
            unsigned tk = ld_relaxed32(ticket_src);
            mbar_wait(w1_bar + 16, W_PAR);
#pragma unroll
            for (int u = 0; u < 2; u++)
#pragma unroll
                for (int T = 0; T < 4; T++) ldsm4t(*(uint32_t(*)[4])(a2 + 16 * u + 4 * T), (w2_a ^ (T * 32)) + u * 2048);
            int n = 0;
            if (tk < (unsigned)NCTA) {
                do {
                    tk = ld_relaxed32(ticket_src);
                    if (++n > SPIN_LIMIT) __trap();
                } while (tk < (unsigned)NCTA);
                if (do_pf) asm volatile("prefetch.global.L2 [%0];" ::"l"(inbox_pf));
                spin_cycles(DELAY1);
                ld_relaxed2x64(ua, p1); ld_relaxed2x64(ub, p1 + 32);
            }
            while (!all_complete(ua, ub)) {
                ld_relaxed2x64(ua, p1); ld_relaxed2x64(ub, p1 + 32);
                if (++n > SPIN_LIMIT) __trap();
            }
            const uint32_t at0 = pack_bf(fx_decode(ua.x, ua.y), fx_decode(ua.z, ua.w)), at1 = pack_bf(fx_decode(ub.x, ub.y), fx_decode(ub.z, ub.w));
            hb0 = pack_bf(bf_lo(xv[0]) + bf_lo(at0), bf_hi(xv[0]) + bf_hi(at0));
            hb1 = pack_bf(bf_lo(xv[1]) + bf_lo(at1), bf_hi(xv[1]) + bf_hi(at1));
        }
        TSTAMP(8);
        gemv1_partial(a1, hb0, hb1, j4, c, a_part);
        {
            const float h0 = bf_lo(hb0), h1 = bf_hi(hb0), h2 = bf_lo(hb1), h3 = bf_hi(hb1);
            const float s1 = (h0 + h1) + (h2 + h3);
            const float s2 = (h0 * h0 + h1 * h1) + (h2 * h2 + h3 * h3);
            float t = ((c & 1) ? s2 : s1) + __shfl_xor_sync(~0u, (c & 1) ? s1 : s2, 1);
            t += __shfl_xor_sync(~0u, t, 2);
            t += __shfl_xor_sync(~0u, t, 8);
            t += __shfl_xor_sync(~0u, t, 16);
            if ((lane & 0x1a) == 0) sts32(a_stat, __float_as_uint(t));
        }
        if (keep_h) {
            sts32(a_keep, hb0);
            sts32(a_keep + 16, hb1);
        }
        cons_sync();
        TSTAMP(9);
        if (warp < 2) {
            const uint4 q0 = lds128(sb + OFF_STAT + warp * 64), q1 = lds128(sb + OFF_STAT + warp * 64 + 16);
            const uint4 q2 = lds128(sb + OFF_STAT + warp * 64 + 32), q3 = lds128(sb + OFF_STAT + warp * 64 + 48);
            const float sacc = sum8(a_sum);
            const float cs = sum8(a_cs);
            const float mean = (((__uint_as_float(q0.x) + __uint_as_float(q0.y)) + (__uint_as_float(q0.z) + __uint_as_float(q0.w))) +
                                ((__uint_as_float(q1.x) + __uint_as_float(q1.y)) + (__uint_as_float(q1.z) + __uint_as_float(q1.w)))) * (1.0f / D_MODEL);
            const float msq = (((__uint_as_float(q2.x) + __uint_as_float(q2.y)) + (__uint_as_float(q2.z) + __uint_as_float(q2.w))) +
                               ((__uint_as_float(q3.x) + __uint_as_float(q3.y)) + (__uint_as_float(q3.z) + __uint_as_float(q3.w)))) * (1.0f / D_MODEL);
            const float var = fmaxf(msq - mean * mean, 0.f);
            float sq, iden;
            asm("sqrt.approx.ftz.f32 %0, %1;" : "=f"(sq) : "f"(rnd_bf(rnd_bf(var) + 1e-5f)));
            asm("rcp.approx.ftz.f32 %0, %1;" : "=f"(iden) : "f"(rnd_bf(sq)));
            const float z = fmaxf(rnd_bf(rnd_bf((sacc - rnd_bf(mean) * cs) * iden) + b1v), 0.f);
            sts16(a_hid, (uint16_t)pack_bf(z * z, 0.f));
        }
        cons_sync();
        uint32_t hb[4];
        ldsm4(hb, a_hidb);
        const float hfin = bf16_at(a_hfin);
        float y[4][4];
#pragma unroll
        for (int T = 0; T < 4; T++) {
            y[T][0] = y[T][1] = y[T][2] = y[T][3] = 0.f;
            mma_bf16(y[T], a2[4 * T], a2[4 * T + 1], a2[4 * T + 2], a2[4 * T + 3], hb[0], hb[1]);
        }
#pragma unroll
        for (int T = 0; T < 4; T++)
            mma_bf16(y[T], a2[16 + 4 * T], a2[16 + 4 * T + 1], a2[16 + 4 * T + 2], a2[16 + 4 * T + 3], hb[2], hb[3]);
        {
            const bool up2 = c & 2, up1 = c & 1;
            uint32_t e[4];
#pragma unroll
            for (int i = 0; i < 4; i++) e[i] = __float_as_uint(up2 ? (up1 ? y[3][i] : y[2][i]) : (up1 ? y[1][i] : y[0][i])) | 1u;
            asm volatile("st.relaxed.gpu.global.v4.u32 [%0], {%1,%2,%3,%4};" ::"l"(part_dst), "r"(e[0]), "r"(e[1]), "r"(e[2]), "r"(e[3]) : "memory");
        }
        TSTAMP(10);
        if (!is_fin) return;
        {
            uint4 u, w;
            int n = 0;
            spin_cycles(DELAY2);
            do {
                ld_relaxed128(u, inbox); ld_relaxed128(w, inbox2);
                if (++n > SPIN_LIMIT) __trap();
            } while (!all_marked(u, w));
            const float v0 = fmaf(__uint_as_float(w.x), wsel, __uint_as_float(u.x)), v1 = fmaf(__uint_as_float(w.y), wsel, __uint_as_float(u.y));
            const float v2 = fmaf(__uint_as_float(w.z), wsel, __uint_as_float(u.z)), v3 = fmaf(__uint_as_float(w.w), wsel, __uint_as_float(u.w));
            const bool up16 = lane & 16, up8 = lane & 8;
            const float r0 = (up16 ? v2 : v0) + __shfl_xor_sync(~0u, up16 ? v0 : v2, 16);
            const float r1 = (up16 ? v3 : v1) + __shfl_xor_sync(~0u, up16 ? v1 : v3, 16);
            const float r = (up8 ? r1 : r0) + __shfl_xor_sync(~0u, up8 ? r0 : r1, 8);
            sts32(a_fin, __float_as_uint(r));
        }
        cons_sync();
        if (warp == 0) {
            const float y2 = sum8(a_sum);
            *out_dst = __ushort_as_bfloat16((unsigned short)pack_bf(hfin + rnd_bf(rnd_bf(y2) + b2v), 0.f));
        }
        if (bh == 0) {
            *(ulonglong2*)(g_acc1 + tid * 4) = make_ulonglong2(0, 0);
            *(ulonglong2*)(g_acc1 + tid * 4 + 2) = make_ulonglong2(0, 0);
            g_ticket[tid] = 0;
        }
        TSTAMP(11);
    }
}

typedef CUresult (*EncodeFn)(CUtensorMap*, CUtensorMapDataType, cuuint32_t, void*, const cuuint64_t*, const cuuint64_t*,
                             const cuuint32_t*, const cuuint32_t*, CUtensorMapInterleave, CUtensorMapSwizzle,
                             CUtensorMapL2promotion, CUtensorMapFloatOOBfill);

void make_map(EncodeFn enc, CUtensorMap* tm, void* ptr, uint64_t cols, uint64_t rows, uint32_t box_cols, uint32_t box_rows,
              CUtensorMapSwizzle swz) {
    const cuuint64_t dims[2] = {cols, rows};
    const cuuint64_t strides[1] = {cols * 2};
    const cuuint32_t box[2] = {box_cols, box_rows};
    const cuuint32_t es[2] = {1, 1};
    enc(tm, CU_TENSOR_MAP_DATA_TYPE_BFLOAT16, 2, ptr, dims, strides, box, es, CU_TENSOR_MAP_INTERLEAVE_NONE, swz,
        CU_TENSOR_MAP_L2_PROMOTION_NONE, CU_TENSOR_MAP_FLOAT_OOB_FILL_NONE);
}

}

extern "C" void kernel_launch(void* const* d_in, const int* in_sizes, int n_in, void* d_out, int out_size) {
    (void)in_sizes; (void)n_in; (void)out_size;
    static EncodeFn enc = nullptr;
    static Scratch* scr = nullptr;
    if (!enc) {
        void* fn = nullptr;
        cudaDriverEntryPointQueryResult qr;
        cudaGetDriverEntryPoint("cuTensorMapEncodeTiled", &fn, cudaEnableDefault, &qr);
        enc = (EncodeFn)fn;
        cudaGetSymbolAddress((void**)&scr, g_scratch);
        cudaFuncSetAttribute(decode_block_kernel, cudaFuncAttributeMaxDynamicSharedMemorySize, SMEM_BYTES);
    }
    Maps tm;
    make_map(enc, &tm.v, d_in[2], 64, (uint64_t)2 * NHEAD * SK * 2, 64, TILE_KEYS * 2, CU_TENSOR_MAP_SWIZZLE_128B);
    make_map(enc, &tm.wq, d_in[3], QCOLS, D_MODEL, 64, 128, CU_TENSOR_MAP_SWIZZLE_128B);
    make_map(enc, &tm.wo, d_in[4], D_MODEL, QCOLS, 64, 128, CU_TENSOR_MAP_SWIZZLE_128B);
    make_map(enc, &tm.w1, d_in[6], FF, D_MODEL, 32, 256, CU_TENSOR_MAP_SWIZZLE_64B);
    make_map(enc, &tm.w2, d_in[8], D_MODEL, FF, 64, 32, CU_TENSOR_MAP_SWIZZLE_128B);
    decode_block_kernel<<<NCTA, NTHREADS, SMEM_BYTES>>>(
        tm, (const __nv_bfloat16*)d_in[0], (const __nv_bfloat16*)d_in[1], (const __nv_bfloat16*)d_in[7],
        (const __nv_bfloat16*)d_in[9], (__nv_bfloat16*)d_out, scr);
}
```

```cpp
#include <cuda_runtime.h>
#include <cuda_bf16.h>
#include <cuda.h>
#include <stdint.h>

namespace {

constexpr int D_MODEL = 512;
constexpr int NHEAD = 32;
constexpr int SK = 8192;
constexpr int DH = 128;
constexpr int FF = 1376;
constexpr int QCOLS = NHEAD * DH;

constexpr int NCTA = 128;
constexpr int KEYS_PER_CTA = SK / 2;
constexpr int TILE_KEYS = 64;
constexpr int TILE_BYTES = TILE_KEYS * DH * 2;
constexpr int NTILE = KEYS_PER_CTA / TILE_KEYS;
#define NST_ 10
#define NINIT_ 4
#define WLATE_ 3
#define WTH_ 40
#define DLY2_ 300
constexpr int NST = NST_;
constexpr int NINIT = NINIT_;
constexpr int WLATE = WLATE_;
constexpr int WTH = WTH_;
constexpr int DELAY2 = DLY2_;
constexpr int NCONS = 256;
constexpr int NTHREADS = NCONS + 64;
constexpr int NMLP = FF / 32;
constexpr int KPRE = NST - 4;
constexpr int T_WQ = 0, T_K0 = 4, T_WO = T_K0 + KPRE, T_K1 = T_WO + 4, T_V = T_K1 + NTILE - KPRE, T_W1 = T_V + NTILE,
              T_W2 = T_W1 + 2, T_END = T_W2 + 2;

constexpr int OFF_RING = 0;
constexpr int OFF_SP = OFF_RING + NST * TILE_BYTES;
constexpr int OFF_PART = OFF_SP + KEYS_PER_CTA * 2;
constexpr int OFF_CS = OFF_PART + 8 * 64 * 4;
constexpr int OFF_XN = OFF_CS + 8 * 64 * 4;
constexpr int OFF_X = OFF_XN + 1024;
constexpr int O_STRIDE = 272;
constexpr int OFF_O = OFF_X + 2048 + 1024 + 64;
constexpr int OFF_Q = OFF_O + 4 * O_STRIDE;
constexpr int OFF_RED = OFF_Q + 256;
constexpr int OFF_STAT = OFF_RED + 64;
constexpr int OFF_HID = OFF_STAT + 128;
constexpr int OFF_ML = OFF_HID + 160;
constexpr int OFF_BAR = OFF_ML + 16;
constexpr int SMEM_USED = OFF_BAR + (2 * NST + 3) * 8;
constexpr int SMEM_BYTES = SMEM_USED + 1024;

constexpr float FX_SCALE = 1073741824.0f;
constexpr float FX_INV = 1.0f / 1073741824.0f;

constexpr int NFIN = 32;
struct Scratch {
    unsigned long long acc1[2 * D_MODEL];
    unsigned int ticket[8 * 32];
    uint4 part[NFIN * NMLP * 8];
};
__device__ __align__(1024) Scratch g_scratch;

#define TSTAMP(i)

__device__ __forceinline__ void mbar_init(uint32_t bar, uint32_t cnt) {
    asm volatile("mbarrier.init.shared::cta.b64 [%0], %1;" ::"r"(bar), "r"(cnt) : "memory");
}
__device__ __forceinline__ void mbar_expect_tx(uint32_t bar, uint32_t bytes) {
    asm volatile("mbarrier.arrive.expect_tx.shared::cta.b64 _, [%0], %1;" ::"r"(bar), "r"(bytes) : "memory");
}
__device__ __forceinline__ void mbar_arrive(uint32_t bar) {
    asm volatile("mbarrier.arrive.shared::cta.b64 _, [%0];" ::"r"(bar) : "memory");
}
__device__ __forceinline__ bool mbar_try(uint32_t bar, uint32_t parity) {
    uint32_t ok;
    asm volatile("{\n.reg .pred p;\nmbarrier.try_wait.parity.shared::cta.b64 p, [%1], %2;\nselp.u32 %0, 1, 0, p;\n}"
                 : "=r"(ok) : "r"(bar), "r"(parity) : "memory");
    return ok;
}
constexpr int SPIN_LIMIT = 1 << 20;
__device__ __forceinline__ void mbar_wait(uint32_t bar, uint32_t parity) {
    int n = 0;
    while (!mbar_try(bar, parity)) { if (++n > SPIN_LIMIT) __trap(); }
}
__device__ __forceinline__ void bulk_load(uint32_t dst, const void* src, uint32_t bytes, uint32_t bar) {
    asm volatile("cp.async.bulk.shared::cluster.global.mbarrier::complete_tx::bytes [%0], [%1], %2, [%3];"
                 ::"r"(dst), "l"(src), "r"(bytes), "r"(bar) : "memory");
}
__device__ __forceinline__ void tma2d(uint32_t dst, const CUtensorMap* tm, int c0, int c1, uint32_t bar) {
    asm volatile("cp.async.bulk.tensor.2d.shared::cluster.global.mbarrier::complete_tx::bytes [%0], [%1, {%3, %4}], [%2];"
                 ::"r"(dst), "l"(tm), "r"(bar), "r"(c0), "r"(c1) : "memory");
}
__device__ __forceinline__ void bulk_load_stream(uint32_t dst, const void* src, uint32_t bytes, uint32_t bar, uint64_t pol) {
    asm volatile("cp.async.bulk.shared::cluster.global.mbarrier::complete_tx::bytes.L2::cache_hint [%0], [%1], %2, [%3], %4;"
                 ::"r"(dst), "l"(src), "r"(bytes), "r"(bar), "l"(pol) : "memory");
}
__device__ __forceinline__ void tma2d_stream(uint32_t dst, const CUtensorMap* tm, int c0, int c1, uint32_t bar, uint64_t pol) {
    asm volatile("cp.async.bulk.tensor.2d.shared::cluster.global.mbarrier::complete_tx::bytes.L2::cache_hint [%0], [%1, {%3, %4}], [%2], %5;"
                 ::"r"(dst), "l"(tm), "r"(bar), "r"(c0), "r"(c1), "l"(pol) : "memory");
}
__device__ __forceinline__ bool elect_one() {
    uint32_t p;
    asm volatile("{\n.reg .pred p;\nelect.sync _|p, 0xffffffff;\nselp.u32 %0, 1, 0, p;\n}" : "=r"(p));
    return p;
}
__device__ __forceinline__ void cons_sync() { asm volatile("bar.sync 1, 256;" ::: "memory"); }

__device__ __forceinline__ uint32_t mapa(uint32_t addr, uint32_t rank) {
    uint32_t r;
    asm("mapa.shared::cluster.u32 %0, %1, %2;" : "=r"(r) : "r"(addr), "r"(rank));
    return r;
}
__device__ __forceinline__ void st_async_b32(uint32_t addr, uint32_t v, uint32_t bar) {
    asm volatile("st.async.weak.shared::cluster.mbarrier::complete_tx::bytes.b32 [%0], %1, [%2];" ::"r"(addr), "r"(v), "r"(bar) : "memory");
}
__device__ __forceinline__ void st_async_v2(uint32_t addr, uint32_t v0, uint32_t v1, uint32_t bar) {
    asm volatile("st.async.weak.shared::cluster.mbarrier::complete_tx::bytes.v2.b32 [%0], {%1, %2}, [%3];" ::"r"(addr), "r"(v0), "r"(v1), "r"(bar) : "memory");
}

__device__ __forceinline__ void mma_bf16(float (&d)[4], uint32_t a0, uint32_t a1, uint32_t a2, uint32_t a3, uint32_t b0, uint32_t b1) {
    asm volatile("mma.sync.aligned.m16n8k16.row.col.f32.bf16.bf16.f32 {%0,%1,%2,%3}, {%4,%5,%6,%7}, {%8,%9}, {%0,%1,%2,%3};"
                 : "+f"(d[0]), "+f"(d[1]), "+f"(d[2]), "+f"(d[3])
                 : "r"(a0), "r"(a1), "r"(a2), "r"(a3), "r"(b0), "r"(b1));
}
__device__ __forceinline__ void ldsm4(uint32_t (&r)[4], uint32_t addr) {
    asm volatile("ldmatrix.sync.aligned.m8n8.x4.shared.b16 {%0,%1,%2,%3}, [%4];"
                 : "=r"(r[0]), "=r"(r[1]), "=r"(r[2]), "=r"(r[3]) : "r"(addr) : "memory");
}
__device__ __forceinline__ void ldsm4t(uint32_t (&r)[4], uint32_t addr) {
    asm volatile("ldmatrix.sync.aligned.m8n8.x4.trans.shared.b16 {%0,%1,%2,%3}, [%4];"
                 : "=r"(r[0]), "=r"(r[1]), "=r"(r[2]), "=r"(r[3]) : "r"(addr) : "memory");
}
__device__ __forceinline__ uint4 lds128(uint32_t a) {
    uint4 v;
    asm volatile("ld.shared.v4.u32 {%0,%1,%2,%3}, [%4];" : "=r"(v.x), "=r"(v.y), "=r"(v.z), "=r"(v.w) : "r"(a) : "memory");
    return v;
}
__device__ __forceinline__ uint2 lds64(uint32_t a) {
    uint2 v;
    asm volatile("ld.shared.v2.u32 {%0,%1}, [%2];" : "=r"(v.x), "=r"(v.y) : "r"(a) : "memory");
    return v;
}
__device__ __forceinline__ uint32_t lds32(uint32_t a) {
    uint32_t v;
    asm volatile("ld.shared.u32 %0, [%1];" : "=r"(v) : "r"(a) : "memory");
    return v;
}
__device__ __forceinline__ void sts128(uint32_t a, uint4 v) {
    asm volatile("st.shared.v4.u32 [%0], {%1,%2,%3,%4};" ::"r"(a), "r"(v.x), "r"(v.y), "r"(v.z), "r"(v.w) : "memory");
}
__device__ __forceinline__ void sts64(uint32_t a, uint32_t v0, uint32_t v1) {
    asm volatile("st.shared.v2.u32 [%0], {%1,%2};" ::"r"(a), "r"(v0), "r"(v1) : "memory");
}
__device__ __forceinline__ void sts32(uint32_t a, uint32_t v) {
    asm volatile("st.shared.u32 [%0], %1;" ::"r"(a), "r"(v) : "memory");
}
__device__ __forceinline__ void sts16(uint32_t a, uint16_t v) {
    asm volatile("st.shared.u16 [%0], %1;" ::"r"(a), "h"(v) : "memory");
}
__device__ __forceinline__ float bf_lo(uint32_t v) { return __uint_as_float(v << 16); }
__device__ __forceinline__ float bf_hi(uint32_t v) { return __uint_as_float(v & 0xffff0000u); }
__device__ __forceinline__ uint32_t pack_bf(float lo, float hi) {
    uint32_t r;
    asm("cvt.rn.bf16x2.f32 %0, %1, %2;" : "=r"(r) : "f"(hi), "f"(lo));
    return r;
}
__device__ __forceinline__ float rnd_bf(float v) { return bf_lo(pack_bf(v, 0.f)); }

__device__ __forceinline__ unsigned long long fx_encode(float v) {
    return ((unsigned long long)__float2ll_rn(v * FX_SCALE) << 8) + 1ull;
}
__device__ __forceinline__ float fx_decode(uint32_t lo, uint32_t hi) {
    return fmaf(__int2float_rn((int)hi), 1.0f / 64.0f, __uint2float_rn(lo & 0xffffff00u) * (FX_INV / 256.0f));
}
__device__ __forceinline__ void spin_cycles(uint32_t n) {
    uint32_t t0, t;
    asm volatile("mov.u32 %0, %%clock;" : "=r"(t0));
    do { asm volatile("mov.u32 %0, %%clock;" : "=r"(t)); } while (t - t0 < n);
}
__device__ __forceinline__ void red_add64(unsigned long long* p, unsigned long long v) {
    asm volatile("red.relaxed.gpu.global.add.u64 [%0], %1;" ::"l"(p), "l"(v) : "memory");
}
__device__ __forceinline__ void ld_relaxed2x64(uint4& v, const void* p) {
    asm volatile("{\n.reg .b64 a, b;\nld.relaxed.gpu.global.v2.b64 {a, b}, [%4];\nmov.b64 {%0, %1}, a;\nmov.b64 {%2, %3}, b;\n}"
                 : "=r"(v.x), "=r"(v.y), "=r"(v.z), "=r"(v.w) : "l"(p) : "memory");
}
__device__ __forceinline__ void ld_relaxed128(uint4& v, const uint4* p) {
    asm volatile("ld.relaxed.gpu.global.v4.u32 {%0,%1,%2,%3}, [%4];" : "=r"(v.x), "=r"(v.y), "=r"(v.z), "=r"(v.w) : "l"(p) : "memory");
}
__device__ __forceinline__ uint32_t and3(uint32_t a, uint32_t b, uint32_t c) {
    uint32_t r;
    asm("lop3.b32 %0, %1, %2, %3, 0x80;" : "=r"(r) : "r"(a), "r"(b), "r"(c));
    return r;
}
__device__ __forceinline__ bool all_marked(const uint4& a, const uint4& b) {
    return __all_sync(~0u, and3(and3(a.x, a.y, a.z), and3(a.w, b.x, b.y), and3(b.z, b.w, 1u)));
}
__device__ __forceinline__ bool all_complete(const uint4& a, const uint4& b) {
    return __all_sync(~0u, and3(and3(a.x, a.z, b.x), b.z, 32u));
}
__device__ __forceinline__ float bf16_at(uint32_t a) {
    uint16_t v;
    asm volatile("ld.shared.u16 %0, [%1];" : "=h"(v) : "r"(a) : "memory");
    return __uint_as_float((uint32_t)v << 16);
}
__device__ __forceinline__ unsigned ld_relaxed32(const unsigned* p) {
    unsigned v;
    asm volatile("ld.relaxed.gpu.global.u32 %0, [%1];" : "=r"(v) : "l"(p) : "memory");
    return v;
}

__device__ __forceinline__ int bpos(int k) { return ((k >> 1) & 3) * 16 + ((k >> 4) & 3) * 4 + ((k >> 3) & 1) * 2 + (k & 1); }

__device__ __forceinline__ void gemv1_partial(const uint32_t* a1, uint32_t hb0, uint32_t hb1, int j, int c, uint32_t a) {
    float t0[4] = {0.f, 0.f, 0.f, 0.f}, t1[4] = {0.f, 0.f, 0.f, 0.f}, t2[4] = {0.f, 0.f, 0.f, 0.f}, t3[4] = {0.f, 0.f, 0.f, 0.f};
#pragma unroll
    for (int k = 0; k < 2; k++) {
        const uint32_t m0 = (j == k) ? hb0 : 0u, m1 = (j == k) ? hb1 : 0u;
        const uint32_t n0 = (j == k + 2) ? hb0 : 0u, n1 = (j == k + 2) ? hb1 : 0u;
        mma_bf16(t0, a1[8 * k], a1[8 * k + 1], a1[8 * k + 2], a1[8 * k + 3], m0, m1);
        mma_bf16(t1, a1[8 * k + 4], a1[8 * k + 5], a1[8 * k + 6], a1[8 * k + 7], m0, m1);
        mma_bf16(t2, a1[8 * k + 16], a1[8 * k + 17], a1[8 * k + 18], a1[8 * k + 19], n0, n1);
        mma_bf16(t3, a1[8 * k + 20], a1[8 * k + 21], a1[8 * k + 22], a1[8 * k + 23], n0, n1);
    }
    const bool up2 = c & 2, up1 = c & 1;
    float r4[4], r2[2];
    const float send[4] = {up2 ? t2[0] : t0[1], up2 ? t2[2] : t0[3], up2 ? t3[0] : t1[1], up2 ? t3[2] : t1[3]};
    const float keep[4] = {up2 ? t2[1] : t0[0], up2 ? t2[3] : t0[2], up2 ? t3[1] : t1[0], up2 ? t3[3] : t1[2]};
#pragma unroll
    for (int i = 0; i < 4; i++) r4[i] = keep[i] + __shfl_xor_sync(~0u, send[i], 2);
#pragma unroll
    for (int i = 0; i < 2; i++) r2[i] = (up1 ? r4[i + 2] : r4[i]) + __shfl_xor_sync(~0u, up1 ? r4[i] : r4[i + 2], 1);
    sts32(a, __float_as_uint(r2[0]));
    sts32(a + 32, __float_as_uint(r2[1]));
}

__device__ __forceinline__ float sum8(uint32_t a) {
    float p[8];
#pragma unroll
    for (int w = 0; w < 8; w++) p[w] = __uint_as_float(lds32(a + w * 256));
    return ((p[0] + p[1]) + (p[2] + p[3])) + ((p[4] + p[5]) + (p[6] + p[7]));
}

struct Maps { CUtensorMap v, wq, wo, w1, w2; };

__global__ void __cluster_dims__(2, 1, 1) __launch_bounds__(NTHREADS, 1)
decode_block_kernel(const __grid_constant__ Maps tm,
                    const __nv_bfloat16* __restrict__ x, const __nv_bfloat16* __restrict__ Kc,
                    const __nv_bfloat16* __restrict__ b1, const __nv_bfloat16* __restrict__ b2,
                    __nv_bfloat16* __restrict__ out, Scratch* __restrict__ scr) {
    unsigned long long* const g_acc1 = scr->acc1;
    unsigned int* const g_ticket = scr->ticket;
    uint4* const g_part = scr->part;
    extern __shared__ unsigned char smem_raw[];
    const uint32_t sb = ((uint32_t)__cvta_generic_to_shared(smem_raw) + 1023u) & ~1023u;
    const uint32_t bar_full = sb + OFF_BAR, bar_empty = bar_full + NST * 8;
    const uint32_t bar_q = bar_empty + NST * 8, bar_ml = bar_q + 8, bar_o = bar_ml + 8;

    TSTAMP(0);
    int tid = threadIdx.x;
    asm volatile("" : "+r"(tid));
    const int lane = tid & 31;
    const int warp = __shfl_sync(~0u, tid >> 5, 0);
    const int bh = blockIdx.x >> 1, rank = blockIdx.x & 1;
    const int b = bh >> 5, h = bh & 31;
    const bool is_mlp = (rank == 0) && (bh < NMLP);
    const int f0 = bh * 32;

    const char* ksrc = (const char*)Kc + (size_t)blockIdx.x * (KEYS_PER_CTA * DH * 2);
    constexpr uint64_t pol = 0x12F0000000000000ull;
    if (elect_one()) {
        if (warp < 6) {
            const int s = warp < 2 ? T_K0 + warp : warp - 2;
            const uint32_t fb = bar_full + s * 8;
            mbar_init(fb, 1);
            asm volatile("fence.mbarrier_init.release.cluster;" ::: "memory");
            mbar_expect_tx(fb, TILE_BYTES);
            if (warp < 2) bulk_load_stream(sb + OFF_RING + s * TILE_BYTES, ksrc + (size_t)warp * TILE_BYTES, TILE_BYTES, fb, pol);
            else tma2d(sb + OFF_RING + s * TILE_BYTES, &tm.wq, h * DH + rank * 64, s * 128, fb);
        } else if (warp == 7) {
#pragma unroll
            for (int s = 0; s < NST; s++) mbar_init(bar_empty + s * 8, 8);
            asm volatile("fence.mbarrier_init.release.cluster;" ::: "memory");
        } else if (warp == 8) {
#pragma unroll
            for (int s = T_K0 + 2; s < NST; s++) mbar_init(bar_full + s * 8, 1);
            asm volatile("fence.mbarrier_init.release.cluster;" ::: "memory");
#pragma unroll
            for (int s = T_K0 + 2; s < T_K0 + NINIT; s++) {
                mbar_expect_tx(bar_full + s * 8, TILE_BYTES);
                bulk_load_stream(sb + OFF_RING + s * TILE_BYTES, ksrc + (size_t)(s - T_K0) * TILE_BYTES, TILE_BYTES, bar_full + s * 8, pol);
            }
        } else if (warp == 9) {
            mbar_init(bar_q, 2); mbar_init(bar_ml, 1); mbar_init(bar_o, 10);
            asm volatile("fence.mbarrier_init.release.cluster;" ::: "memory");
            mbar_expect_tx(bar_q, 128);
            mbar_expect_tx(bar_ml, is_mlp ? 8 + 2048 + 1024 + 64 : 8);
            if (is_mlp) {
                bulk_load(sb + OFF_X, x, 2048, bar_ml);
                bulk_load(sb + OFF_X + 2048, b2, 1024, bar_ml);
                bulk_load(sb + OFF_X + 3072, b1 + f0, 64, bar_ml);
            }
            mbar_expect_tx(bar_o, 512);
            asm volatile("prefetch.tensormap [%0];" ::"l"(&tm.wo) : "memory");
            asm volatile("prefetch.tensormap [%0];" ::"l"(&tm.v) : "memory");
            asm volatile("prefetch.tensormap [%0];" ::"l"(&tm.w1) : "memory");
            asm volatile("prefetch.tensormap [%0];" ::"l"(&tm.w2) : "memory");
        }
    }
    __syncwarp();
    asm volatile("barrier.cluster.arrive.relaxed.aligned;" ::: "memory");

    if (warp == 8) {
        asm volatile("barrier.cluster.wait.aligned;" ::: "memory");
        if (lane == 0) {
#pragma unroll
            for (int w = 0; w < 4; w++) mbar_wait(bar_full + (T_WQ + w) * 8, 0);
#pragma unroll
            for (int k = NINIT; k < KPRE; k++) {
                const uint32_t fb = bar_full + (T_K0 + k) * 8;
                mbar_expect_tx(fb, TILE_BYTES);
                bulk_load_stream(sb + OFF_RING + (T_K0 + k) * TILE_BYTES, ksrc + (size_t)k * TILE_BYTES, TILE_BYTES, fb, pol);
            }
            const int vline0 = (bh * SK + rank * KEYS_PER_CTA) * 2;
            const int tend = is_mlp ? T_END : T_W1;
            int st = 0, ph = 0;
#pragma unroll 1
            for (int t = NST; t < tend; t++) {
                const uint32_t dst = sb + OFF_RING + st * TILE_BYTES, fb = bar_full + st * 8;
                mbar_wait(bar_empty + st * 8, ph);
                if (t == T_W1) {
                    int n = 0;
                    while (ld_relaxed32(g_ticket) < (unsigned)WTH) { if (++n > SPIN_LIMIT) __trap(); }
                    mbar_wait(bar_full + ((T_W1 - 1 - WLATE) % NST) * 8, ((T_W1 - 1 - WLATE) / NST) & 1);
                }
                mbar_expect_tx(fb, TILE_BYTES);
                if (t < T_K1) {
                    tma2d(dst, &tm.wo, rank * 256 + (t - T_WO) * 64, h * DH, fb);
                } else if (t < T_V) {
                    bulk_load_stream(dst, ksrc + (size_t)(t - 8) * TILE_BYTES, TILE_BYTES, fb, pol);
                } else if (t < T_W1) {
                    tma2d_stream(dst, &tm.v, 0, vline0 + (t - T_V) * (TILE_KEYS * 2), fb, pol);
                } else if (t < T_W2) {
                    tma2d(dst, &tm.w1, f0, (t - T_W1) * 256, fb);
                } else {
#pragma unroll
                    for (int i = 0; i < 4; i++) tma2d(dst + i * 4096, &tm.w2, ((t - T_W2) * 4 + i) * 64, f0, fb);
                }
                if (++st == NST) { st = 0; ph ^= 1; }
            }
        }
        return;
    }

    if (warp == 9) {
        if (is_mlp) {
#pragma unroll
            for (int i = 0; i < 8; i++) g_part[((i * 4 + (lane >> 3)) * NMLP + bh) * 8 + (lane & 7)] = make_uint4(0, 0, 0, 0);
            __threadfence();
        }
        asm volatile("barrier.cluster.wait.aligned;" ::: "memory");
        if (lane == 0) mbar_arrive(bar_o);
        return;
    }

    const int g = lane >> 2, c = lane & 3;
    const int rr = lane & 7, mi = lane >> 3;
    const int mb_ = g & 1, j4 = g >> 1;
    const int d0 = warp * 64 + j4 * 16 + c * 2;
    uint32_t qa[16], wf[64];
    {
        if (warp == 6) {
            const uint4 xa0 = __ldg((const uint4*)(x + b * D_MODEL) + lane), xa1 = __ldg((const uint4*)(x + b * D_MODEL) + 32 + lane);
            const uint32_t xa[8] = {xa0.x, xa0.y, xa0.z, xa0.w, xa1.x, xa1.y, xa1.z, xa1.w};
            float s = 0.f;
#pragma unroll
            for (int i = 0; i < 8; i++) s += bf_lo(xa[i]) + bf_hi(xa[i]);
#pragma unroll
            for (int o = 16; o; o >>= 1) s += __shfl_xor_sync(~0u, s, o);
            const float mean = s * (1.0f / D_MODEL);
            float v = 0.f;
#pragma unroll
            for (int i = 0; i < 8; i++) { const float e0 = bf_lo(xa[i]) - mean, e1 = bf_hi(xa[i]) - mean; v += e0 * e0 + e1 * e1; }
#pragma unroll
            for (int o = 16; o; o >>= 1) v += __shfl_xor_sync(~0u, v, o);
            const float mb = rnd_bf(mean);
            const float den = rnd_bf(sqrtf(rnd_bf(rnd_bf(v * (1.0f / D_MODEL)) + 1e-5f)));
#pragma unroll
            for (int i = 0; i < 8; i++) {
                const int k = (i >> 2) * 256 + lane * 8 + (i & 3) * 2;
                sts32(sb + OFF_XN + ((k & ~63) + bpos(k)) * 2,
                      pack_bf(__fdiv_rn(rnd_bf(bf_lo(xa[i]) - mb), den), __fdiv_rn(rnd_bf(bf_hi(xa[i]) - mb), den)));
            }
        }
        asm volatile("barrier.cluster.wait.aligned;" ::: "memory");
        TSTAMP(12);
        cons_sync();

        float q0[4] = {0.f, 0.f, 0.f, 0.f}, q1[4] = {0.f, 0.f, 0.f, 0.f};
        const uint32_t aoff = ((warp >> 2) * 64 + (mi >> 1) * 8 + rr) * 128 + (((warp & 3) * 2 + (mi & 1)) ^ rr) * 16;
#pragma unroll
        for (int t = 0; t < 4; t++) {
            const uint32_t xaddr = sb + OFF_XN + (t * 2 + (warp >> 2)) * 128 + c * 32;
            const uint4 p0 = lds128(xaddr), p1 = lds128(xaddr + 16);
            const uint32_t base = sb + OFF_RING + (T_WQ + t) * TILE_BYTES + aoff;
            mbar_wait(bar_full + (T_WQ + t) * 8, 0);
            uint32_t a0[4], a1[4], a2[4], a3[4];
            ldsm4t(a0, base); ldsm4t(a1, base + 2048); ldsm4t(a2, base + 4096); ldsm4t(a3, base + 6144);
            mma_bf16(q0, a0[0], a0[1], a0[2], a0[3], p0.x, p0.y);
            mma_bf16(q1, a1[0], a1[1], a1[2], a1[3], p0.z, p0.w);
            mma_bf16(q0, a2[0], a2[1], a2[2], a2[3], p1.x, p1.y);
            mma_bf16(q1, a3[0], a3[1], a3[2], a3[3], p1.z, p1.w);
            __syncwarp();
            if (lane == 0) mbar_arrive(bar_empty + (T_WQ + t) * 8);
        }
        TSTAMP(13);
        if (c < 2) sts32(sb + OFF_PART + (warp * 16 + c * 8 + g) * 4, __float_as_uint(c ? q0[2] + q1[2] : q0[0] + q1[0]));
        cons_sync();
        if (warp == 0) {
            const uint2 u = lds64(sb + OFF_PART + lane * 8), w = lds64(sb + OFF_PART + 256 + lane * 8);
            const uint32_t qq = pack_bf(__uint_as_float(u.x) + __uint_as_float(w.x), __uint_as_float(u.y) + __uint_as_float(w.y));
            const uint32_t dst = sb + OFF_Q + rank * 128 + lane * 4;
            sts32(dst, qq);
            st_async_b32(mapa(dst, rank ^ 1), qq, mapa(bar_q, rank ^ 1));
            __syncwarp();
            if (lane == 0) mbar_arrive(bar_q);
        }
        mbar_wait(bar_q, 0);
#pragma unroll
        for (int j = 0; j < 16; j++) qa[j] = lds32(sb + OFF_Q + ((j & 8) + ((g + j) & 7)) * 16 + c * 4);
    }
    TSTAMP(1);

    int st = T_K0, ph = 0;
    float mx = -INFINITY;
    {
        uint32_t koff0 = sb + OFF_RING + (warp * 8 + rr) * 256 + ((rr + mi) & 7) * 16;
        uint32_t koff1 = sb + OFF_RING + (warp * 8 + rr) * 256 + ((rr + mi + 4) & 7) * 16;
        asm volatile("" : "+r"(koff0), "+r"(koff1));
        const bool valid = (c == (g >> 1));
        uint32_t spos = sb + OFF_SP + bpos(warp * 8 + g) * 2;
        auto k_tiles = [&](int n) {
#pragma unroll 1
            for (int i = 0; i < n; i++) {
                const uint32_t base = st * TILE_BYTES;
                mbar_wait(bar_full + st * 8, ph);
                uint32_t k0[4], k1[4], k2[4], k3[4];
                ldsm4(k0, base + koff0); ldsm4(k1, base + koff1);
                ldsm4(k2, base + koff0 + 128); ldsm4(k3, base + koff1 + 128);
                float s0[4] = {0.f, 0.f, 0.f, 0.f}, s1[4] = {0.f, 0.f, 0.f, 0.f};
                mma_bf16(s0, qa[0], qa[2], qa[1], qa[3], k0[0], k0[1]);
                mma_bf16(s1, qa[0], qa[2], qa[1], qa[3], k0[2], k0[3]);
                mma_bf16(s0, qa[4], qa[6], qa[5], qa[7], k1[0], k1[1]);
                mma_bf16(s1, qa[4], qa[6], qa[5], qa[7], k1[2], k1[3]);
                mma_bf16(s0, qa[8], qa[10], qa[9], qa[11], k2[0], k2[1]);
                mma_bf16(s1, qa[8], qa[10], qa[9], qa[11], k2[2], k2[3]);
                mma_bf16(s0, qa[12], qa[14], qa[13], qa[15], k3[0], k3[1]);
                mma_bf16(s1, qa[12], qa[14], qa[13], qa[15], k3[2], k3[3]);
                __syncwarp();
                if (lane == 0) mbar_arrive(bar_empty + st * 8);
                const float raw = (g & 1) ? s0[1] + s1[3] : s0[0] + s1[2];
                const uint32_t sc = pack_bf(rnd_bf(raw) * 0.08838834764831845f, 0.f);
                if (valid) { sts16(spos, (uint16_t)sc); mx = fmaxf(mx, bf_lo(sc)); }
                spos += TILE_KEYS * 2;
                if (++st == NST) { st = 0; ph ^= 1; }
            }
        };
        k_tiles(KPRE);
        {
            static_assert(T_WO == NST, "wo tiles sit in slots 0..3, second pass");
            const int s = warp >> 1;
            const int row = (mi >> 1) * 4 + (rr >> 1) + (rr & 1) * 8;
            const uint32_t base = sb + OFF_RING + s * TILE_BYTES + row * 128;
            const uint32_t c0 = (((mi & 1) * 2 + (warp & 1)) ^ (row & 7)) * 16, c1 = c0 ^ 64;
            mbar_wait(bar_full + s * 8, 1);
#pragma unroll
            for (int t = 0; t < 8; t++) {
                ldsm4t(*(uint32_t(*)[4])(wf + 8 * t), base + t * 2048 + c0);
                ldsm4t(*(uint32_t(*)[4])(wf + 8 * t + 4), base + t * 2048 + c1);
            }
            __syncwarp();
            if (lane < 4) mbar_arrive(bar_empty + lane * 8);
            st = 4;
        }
        k_tiles(NTILE - KPRE);
    }
    TSTAMP(2);
    {
#pragma unroll
        for (int o = 16; o; o >>= 1) mx = fmaxf(mx, __shfl_xor_sync(~0u, mx, o));
        if (lane == 0) sts32(sb + OFF_RED + warp * 4, __float_as_uint(mx));
        cons_sync();
        const uint4 m0 = lds128(sb + OFF_RED), m1 = lds128(sb + OFF_RED + 16);
        const float mloc = fmaxf(fmaxf(fmaxf(__uint_as_float(m0.x), __uint_as_float(m0.y)), fmaxf(__uint_as_float(m0.z), __uint_as_float(m0.w))),
                                 fmaxf(fmaxf(__uint_as_float(m1.x), __uint_as_float(m1.y)), fmaxf(__uint_as_float(m1.z), __uint_as_float(m1.w))));
        const uint4 s0 = lds128(sb + OFF_SP + tid * 16), s1 = lds128(sb + OFF_SP + 4096 + tid * 16);
        const uint32_t sv[8] = {s0.x, s0.y, s0.z, s0.w, s1.x, s1.y, s1.z, s1.w};
        constexpr float LOG2E = 1.4426950408889634f;
        float l = 0.f;
#pragma unroll
        for (int i = 0; i < 8; i++) l += exp2f((bf_lo(sv[i]) - mloc) * LOG2E) + exp2f((bf_hi(sv[i]) - mloc) * LOG2E);
#pragma unroll
        for (int o = 16; o; o >>= 1) l += __shfl_xor_sync(~0u, l, o);
        if (lane == 0) sts32(sb + OFF_RED + 32 + warp * 4, __float_as_uint(l));
        cons_sync();
        const uint4 l0 = lds128(sb + OFF_RED + 32), l1 = lds128(sb + OFF_RED + 48);
        const float lloc = ((__uint_as_float(l0.x) + __uint_as_float(l0.y)) + (__uint_as_float(l0.z) + __uint_as_float(l0.w))) +
                           ((__uint_as_float(l1.x) + __uint_as_float(l1.y)) + (__uint_as_float(l1.z) + __uint_as_float(l1.w)));
        if (tid == 0) st_async_v2(mapa(sb + OFF_ML, rank ^ 1), __float_as_uint(mloc), __float_as_uint(lloc), mapa(bar_ml, rank ^ 1));
        mbar_wait(bar_ml, 0);
        const uint2 pml = lds64(sb + OFF_ML);
        const float mp = __uint_as_float(pml.x), lp = __uint_as_float(pml.y);
        const float M = fmaxf(mloc, mp);
        const float m_a = rank ? mp : mloc, l_a = rank ? lp : lloc, m_b = rank ? mloc : mp, l_b = rank ? lloc : lp;
        const float L = l_a * exp2f((m_a - M) * LOG2E) + l_b * exp2f((m_b - M) * LOG2E);
        const float inv = 1.0f / L;
        uint32_t pv[8];
#pragma unroll
        for (int i = 0; i < 8; i++)
            pv[i] = pack_bf(exp2f((bf_lo(sv[i]) - M) * LOG2E) * inv, exp2f((bf_hi(sv[i]) - M) * LOG2E) * inv);
        sts128(sb + OFF_SP + tid * 16, make_uint4(pv[0], pv[1], pv[2], pv[3]));
        sts128(sb + OFF_SP + 4096 + tid * 16, make_uint4(pv[4], pv[5], pv[6], pv[7]));
        cons_sync();
    }
    TSTAMP(3);
    unsigned long long* acc1_dst = g_acc1 + b * D_MODEL + rank * 256 + warp * 32 + c * 8 + g;
    unsigned* ticket_dst = g_ticket + (tid & 7) * 32;
    uint32_t o_dst = sb + OFF_O + (rank * 2 + (c & 1)) * O_STRIDE + (warp * 8 + g) * 4, o_bar = bar_o;
    if (c & 2) { o_dst = mapa(o_dst, rank ^ 1); o_bar = mapa(bar_o, rank ^ 1); }
    uint32_t o_src = sb + OFF_O + (rr & 3) * O_STRIDE + mi * 16;
    asm volatile("" : "+l"(acc1_dst), "+l"(ticket_dst), "+r"(o_dst), "+r"(o_bar), "+r"(o_src));
    const bool is_fin = bh < NFIN;
    const unsigned* ticket_src = g_ticket + warp * 32;
    const unsigned long long* p1 = g_acc1 + mb_ * D_MODEL + warp * 64 + j4 * 8 + c * 2;
    uint4* part_dst = g_part + ((warp * 4 + c) * NMLP + bh) * 8 + g;
    const uint4* inbox = g_part + bh * (NMLP * 8) + tid;
    const uint4* inbox2 = tid < (NMLP - 32) * 8 ? inbox + 256 : inbox;
    const uint4* inbox_pf = g_part + (bh * NMLP + tid) * 8;
    int do_pf = is_fin && tid < NMLP;
    float wsel = tid < (NMLP - 32) * 8 ? 1.0f : 0.0f;
    __nv_bfloat16* out_dst = out + ((lane >> 3) & 1) * D_MODEL + bh * 16 + (lane >> 4) * 8 + (lane & 7);
    asm volatile("" : "+l"(ticket_src), "+l"(p1), "+l"(part_dst), "+l"(inbox), "+l"(inbox2), "+l"(inbox_pf), "+r"(do_pf), "+f"(wsel), "+l"(out_dst));
    uint32_t xv[2] = {lds32(sb + OFF_X + (mb_ * D_MODEL + d0) * 2), lds32(sb + OFF_X + (mb_ * D_MODEL + d0 + 8) * 2)};
    float b1v = bf16_at(sb + OFF_X + 3072 + lane * 2);
    float b2v = bf16_at(sb + OFF_X + 2048 + ((bh & 31) * 16 + (lane >> 4) * 8 + (lane & 7)) * 2);
    uint32_t a_part = sb + OFF_PART + warp * 256 + ((c >> 1) * 32 + (c & 1) * 16 + g) * 4;
    uint32_t a_stat = sb + OFF_STAT + (mb_ * 16 + (c & 1) * 8 + warp) * 4;
    uint32_t a_keep = sb + OFF_RED + mb_ * 32 + c * 4;
    uint32_t a_sum = sb + OFF_PART + (warp * 32 + lane) * 4, a_cs = sb + OFF_CS + lane * 4;
    uint32_t a_hid = sb + OFF_HID + warp * 80 + lane * 2, a_hidb = sb + OFF_HID + (rr & 1) * 80 + mi * 16;
    uint32_t a_fin = sb + OFF_PART + warp * 256 + lane * 4;
    uint32_t a_hfin = sb + OFF_RED + ((lane >> 3) & 1) * 32 + ((lane >> 4) * 8 + (lane & 7)) * 2;
    int keep_h = warp * 4 + j4 == bh;
    asm volatile("" : "+r"(a_part), "+r"(a_stat), "+r"(a_keep), "+r"(a_sum), "+r"(a_cs), "+r"(a_hid), "+r"(a_hidb), "+r"(a_fin), "+r"(a_hfin),
                 "+r"(keep_h), "+f"(b1v), "+f"(b2v));
    static_assert(T_W1 % NST + 3 < NST, "w1/w2 occupy four consecutive slots with the same parity");
    constexpr int W_PAR = (T_W1 / NST) & 1;
    uint32_t w1_bar = bar_full + (T_W1 % NST + (warp >> 2)) * 8;
    uint32_t w1_a = sb + OFF_RING + (T_W1 % NST + (warp >> 2)) * TILE_BYTES + ((warp & 3) * 64 + (mi >> 1) * 8 + rr) * 64 + ((mi & 1) ^ (rr >> 1)) * 16;
    uint32_t w2_a = sb + OFF_RING + (T_W2 % NST + (warp >> 2)) * TILE_BYTES + (warp & 3) * 4096 + ((mi >> 1) * 8 + rr) * 128 + ((mi & 1) ^ rr) * 16;
    asm volatile("" : "+r"(w1_bar), "+r"(w1_a), "+r"(w2_a));
    {
        const int hh = warp >> 2, ch = 2 * (warp & 3);
        const int line = 2 * (8 * (mi >> 1) + rr) + hh;
        uint32_t voff = sb + OFF_RING + line * 128 + (((ch ^ (mi & 1) ^ (rr >> 2)) ^ (line & 7)) * 16);
        uint32_t pmask = ((c >> 1) == (g & 1)) ? 0xffffffffu : 0u;
        asm volatile("" : "+r"(voff), "+r"(pmask));
        uint32_t paddr = sb + OFF_SP + c * 32;
        float o0[4] = {0.f, 0.f, 0.f, 0.f}, o1[4] = {0.f, 0.f, 0.f, 0.f};
#pragma unroll 1
        for (int i = 0; i < NTILE; i++) {
            const uint32_t base = voff + st * TILE_BYTES;
            uint4 p0 = lds128(paddr), p1 = lds128(paddr + 16);
            p0.x &= pmask; p0.y &= pmask; p0.z &= pmask; p0.w &= pmask;
            p1.x &= pmask; p1.y &= pmask; p1.z &= pmask; p1.w &= pmask;
            asm volatile("" : "+r"(p0.x), "+r"(p0.y), "+r"(p0.z), "+r"(p0.w), "+r"(p1.x), "+r"(p1.y), "+r"(p1.z), "+r"(p1.w));
            mbar_wait(bar_full + st * 8, ph);
            uint32_t a0[4], a1[4], a2[4], a3[4];
            ldsm4t(a0, base); ldsm4t(a1, base + 4096); ldsm4t(a2, base + 8192); ldsm4t(a3, base + 12288);
            if (i == NTILE - 1 && tid < 8) asm volatile("red.relaxed.gpu.global.add.u32 [%0], 1;" ::"l"(ticket_dst) : "memory");
            mma_bf16(o0, a0[0], a0[1], a0[2], a0[3], p0.x, p0.y);
            mma_bf16(o1, a1[0], a1[1], a1[2], a1[3], p0.z, p0.w);
            mma_bf16(o0, a2[0], a2[1], a2[2], a2[3], p1.x, p1.y);
            mma_bf16(o1, a3[0], a3[1], a3[2], a3[3], p1.z, p1.w);
            __syncwarp();
            if (lane == 0) mbar_arrive(bar_empty + st * 8);
            paddr += TILE_KEYS * 2;
            if (++st == NST) { st = 0; ph ^= 1; }
        }
        TSTAMP(4);
        const float v0 = (o0[0] + o1[0]) + (o0[3] + o1[3]);
        const float v1 = (o0[1] + o1[1]) + (o0[2] + o1[2]);
        const uint32_t hi = pack_bf(v0, v1);
        const uint32_t val = (c & 1) ? pack_bf(v0 - bf_lo(hi), v1 - bf_hi(hi)) : hi;
        if (c & 2) st_async_b32(o_dst, val, o_bar);
        else sts32(o_dst, val);
        __syncwarp();
        if (lane == 0) mbar_arrive(bar_o);
        mbar_wait(bar_o, 0);
    }
    TSTAMP(5);
    {
        float d00[4] = {0.f, 0.f, 0.f, 0.f}, d01[4] = {0.f, 0.f, 0.f, 0.f}, d10[4] = {0.f, 0.f, 0.f, 0.f}, d11[4] = {0.f, 0.f, 0.f, 0.f};
        uint32_t ob[4][4];
#pragma unroll
        for (int t = 0; t < 4; t++) ldsm4(ob[t], o_src + t * 64);
#pragma unroll
        for (int t = 0; t < 4; t++) {
            mma_bf16(d00, wf[16 * t], wf[16 * t + 1], wf[16 * t + 2], wf[16 * t + 3], ob[t][0], ob[t][1]);
            mma_bf16(d10, wf[16 * t + 4], wf[16 * t + 5], wf[16 * t + 6], wf[16 * t + 7], ob[t][0], ob[t][1]);
            mma_bf16(d01, wf[16 * t + 8], wf[16 * t + 9], wf[16 * t + 10], wf[16 * t + 11], ob[t][2], ob[t][3]);
            mma_bf16(d11, wf[16 * t + 12], wf[16 * t + 13], wf[16 * t + 14], wf[16 * t + 15], ob[t][2], ob[t][3]);
        }
        const float e0 = (d00[0] + d01[0]) + (d00[1] + d01[1]), e1 = (d00[2] + d01[2]) + (d00[3] + d01[3]);
        const float e2 = (d10[0] + d11[0]) + (d10[1] + d11[1]), e3 = (d10[2] + d11[2]) + (d10[3] + d11[3]);
        const float ea = (c & 2) ? e2 : e0, eb = (c & 2) ? e3 : e1;
        const float e = ((c & 1) ? eb : ea) + __shfl_xor_sync(~0u, (c & 1) ? ea : eb, 1);
        red_add64(acc1_dst, fx_encode(e));
    }
    TSTAMP(6);
    if (!is_mlp) return;

    {
        if (do_pf) asm volatile("prefetch.global.L2 [%0];" ::"l"(inbox_pf));
        uint32_t* a1 = wf;
        uint32_t* a2 = wf + 32;
        mbar_wait(w1_bar, W_PAR);
#pragma unroll
        for (int k = 0; k < 4; k++) {
            ldsm4t(*(uint32_t(*)[4])(a1 + 8 * k), w1_a + k * 1024);
            ldsm4t(*(uint32_t(*)[4])(a1 + 8 * k + 4), (w1_a ^ 32) + k * 1024);
        }
        gemv1_partial(a1, 0x3f803f80u, 0x3f803f80u, j4, c, a_part + (OFF_CS - OFF_PART));
        TSTAMP(7);
        uint32_t hb0, hb1;
        {
            uint4 ua, ub;
            ld_relaxed2x64(ua, p1); ld_relaxed2x64(ub, p1 + 32);
            unsigned tk = ld_relaxed32(ticket_src);
            mbar_wait(w1_bar + 16, W_PAR);
#pragma unroll
            for (int u = 0; u < 2; u++)
#pragma unroll
                for (int T = 0; T < 4; T++) ldsm4t(*(uint32_t(*)[4])(a2 + 16 * u + 4 * T), (w2_a ^ (T * 32)) + u * 2048);
            int n = 0;
            if (tk < (unsigned)NCTA) {
                do {
                    tk = ld_relaxed32(ticket_src);
                    if (++n > SPIN_LIMIT) __trap();
                } while (tk < (unsigned)NCTA);
                if (do_pf) asm volatile("prefetch.global.L2 [%0];" ::"l"(inbox_pf));
                ld_relaxed2x64(ua, p1); ld_relaxed2x64(ub, p1 + 32);
            }
            while (!all_complete(ua, ub)) {
                ld_relaxed2x64(ua, p1); ld_relaxed2x64(ub, p1 + 32);
                if (++n > SPIN_LIMIT) __trap();
            }
            const uint32_t at0 = pack_bf(fx_decode(ua.x, ua.y), fx_decode(ua.z, ua.w)), at1 = pack_bf(fx_decode(ub.x, ub.y), fx_decode(ub.z, ub.w));
            hb0 = pack_bf(bf_lo(xv[0]) + bf_lo(at0), bf_hi(xv[0]) + bf_hi(at0));
            hb1 = pack_bf(bf_lo(xv[1]) + bf_lo(at1), bf_hi(xv[1]) + bf_hi(at1));
        }
        TSTAMP(8);
        gemv1_partial(a1, hb0, hb1, j4, c, a_part);
        {
            const float h0 = bf_lo(hb0), h1 = bf_hi(hb0), h2 = bf_lo(hb1), h3 = bf_hi(hb1);
            const float s1 = (h0 + h1) + (h2 + h3);
            const float s2 = (h0 * h0 + h1 * h1) + (h2 * h2 + h3 * h3);
            float t = ((c & 1) ? s2 : s1) + __shfl_xor_sync(~0u, (c & 1) ? s1 : s2, 1);
            t += __shfl_xor_sync(~0u, t, 2);
            t += __shfl_xor_sync(~0u, t, 8);
            t += __shfl_xor_sync(~0u, t, 16);
            if ((lane & 0x1a) == 0) sts32(a_stat, __float_as_uint(t));
        }
        if (keep_h) {
            sts32(a_keep, hb0);
            sts32(a_keep + 16, hb1);
        }
        cons_sync();
        TSTAMP(9);
        if (warp < 2) {
            const uint4 q0 = lds128(sb + OFF_STAT + warp * 64), q1 = lds128(sb + OFF_STAT + warp * 64 + 16);
            const uint4 q2 = lds128(sb + OFF_STAT + warp * 64 + 32), q3 = lds128(sb + OFF_STAT + warp * 64 + 48);
            const float sacc = sum8(a_sum);
            const float cs = sum8(a_cs);
            const float mean = (((__uint_as_float(q0.x) + __uint_as_float(q0.y)) + (__uint_as_float(q0.z) + __uint_as_float(q0.w))) +
                                ((__uint_as_float(q1.x) + __uint_as_float(q1.y)) + (__uint_as_float(q1.z) + __uint_as_float(q1.w)))) * (1.0f / D_MODEL);
            const float msq = (((__uint_as_float(q2.x) + __uint_as_float(q2.y)) + (__uint_as_float(q2.z) + __uint_as_float(q2.w))) +
                               ((__uint_as_float(q3.x) + __uint_as_float(q3.y)) + (__uint_as_float(q3.z) + __uint_as_float(q3.w)))) * (1.0f / D_MODEL);
            const float var = fmaxf(msq - mean * mean, 0.f);
            float sq, iden;
            asm("sqrt.approx.ftz.f32 %0, %1;" : "=f"(sq) : "f"(rnd_bf(rnd_bf(var) + 1e-5f)));
            asm("rcp.approx.ftz.f32 %0, %1;" : "=f"(iden) : "f"(rnd_bf(sq)));
            const float z = fmaxf(rnd_bf(rnd_bf((sacc - rnd_bf(mean) * cs) * iden) + b1v), 0.f);
            sts16(a_hid, (uint16_t)pack_bf(z * z, 0.f));
        }
        cons_sync();
        uint32_t hb[4];
        ldsm4(hb, a_hidb);
        const float hfin = bf16_at(a_hfin);
        float y[4][4];
#pragma unroll
        for (int T = 0; T < 4; T++) {
            y[T][0] = y[T][1] = y[T][2] = y[T][3] = 0.f;
            mma_bf16(y[T], a2[4 * T], a2[4 * T + 1], a2[4 * T + 2], a2[4 * T + 3], hb[0], hb[1]);
        }
#pragma unroll
        for (int T = 0; T < 4; T++)
            mma_bf16(y[T], a2[16 + 4 * T], a2[16 + 4 * T + 1], a2[16 + 4 * T + 2], a2[16 + 4 * T + 3], hb[2], hb[3]);
        {
            const bool up2 = c & 2, up1 = c & 1;
            uint32_t e[4];
#pragma unroll
            for (int i = 0; i < 4; i++) e[i] = __float_as_uint(up2 ? (up1 ? y[3][i] : y[2][i]) : (up1 ? y[1][i] : y[0][i])) | 1u;
            asm volatile("st.relaxed.gpu.global.v4.u32 [%0], {%1,%2,%3,%4};" ::"l"(part_dst), "r"(e[0]), "r"(e[1]), "r"(e[2]), "r"(e[3]) : "memory");
        }
        TSTAMP(10);
        if (!is_fin) return;
        {
            uint4 u, w;
            int n = 0;
            spin_cycles(DELAY2);
            do {
                ld_relaxed128(u, inbox); ld_relaxed128(w, inbox2);
                if (++n > SPIN_LIMIT) __trap();
            } while (!all_marked(u, w));
            const float v0 = fmaf(__uint_as_float(w.x), wsel, __uint_as_float(u.x)), v1 = fmaf(__uint_as_float(w.y), wsel, __uint_as_float(u.y));
            const float v2 = fmaf(__uint_as_float(w.z), wsel, __uint_as_float(u.z)), v3 = fmaf(__uint_as_float(w.w), wsel, __uint_as_float(u.w));
            const bool up16 = lane & 16, up8 = lane & 8;
            const float r0 = (up16 ? v2 : v0) + __shfl_xor_sync(~0u, up16 ? v0 : v2, 16);
            const float r1 = (up16 ? v3 : v1) + __shfl_xor_sync(~0u, up16 ? v1 : v3, 16);
            const float r = (up8 ? r1 : r0) + __shfl_xor_sync(~0u, up8 ? r0 : r1, 8);
            sts32(a_fin, __float_as_uint(r));
        }
        cons_sync();
        if (warp == 0) {
            const float y2 = sum8(a_sum);
            *out_dst = __ushort_as_bfloat16((unsigned short)pack_bf(hfin + rnd_bf(rnd_bf(y2) + b2v), 0.f));
        }
        if (bh == 0) {
            *(ulonglong2*)(g_acc1 + tid * 4) = make_ulonglong2(0, 0);
            *(ulonglong2*)(g_acc1 + tid * 4 + 2) = make_ulonglong2(0, 0);
            g_ticket[tid] = 0;
        }
        TSTAMP(11);
    }
}

typedef CUresult (*EncodeFn)(CUtensorMap*, CUtensorMapDataType, cuuint32_t, void*, const cuuint64_t*, const cuuint64_t*,
                             const cuuint32_t*, const cuuint32_t*, CUtensorMapInterleave, CUtensorMapSwizzle,
                             CUtensorMapL2promotion, CUtensorMapFloatOOBfill);

void make_map(EncodeFn enc, CUtensorMap* tm, void* ptr, uint64_t cols, uint64_t rows, uint32_t box_cols, uint32_t box_rows,
              CUtensorMapSwizzle swz) {
    const cuuint64_t dims[2] = {cols, rows};
    const cuuint64_t strides[1] = {cols * 2};
    const cuuint32_t box[2] = {box_cols, box_rows};
    const cuuint32_t es[2] = {1, 1};
    enc(tm, CU_TENSOR_MAP_DATA_TYPE_BFLOAT16, 2, ptr, dims, strides, box, es, CU_TENSOR_MAP_INTERLEAVE_NONE, swz,
        CU_TENSOR_MAP_L2_PROMOTION_NONE, CU_TENSOR_MAP_FLOAT_OOB_FILL_NONE);
}

}

extern "C" void kernel_launch(void* const* d_in, const int* in_sizes, int n_in, void* d_out, int out_size) {
    (void)in_sizes; (void)n_in; (void)out_size;
    static EncodeFn enc = nullptr;
    static Scratch* scr = nullptr;
    if (!enc) {
        void* fn = nullptr;
        cudaDriverEntryPointQueryResult qr;
        cudaGetDriverEntryPoint("cuTensorMapEncodeTiled", &fn, cudaEnableDefault, &qr);
        enc = (EncodeFn)fn;
        cudaGetSymbolAddress((void**)&scr, g_scratch);
        cudaFuncSetAttribute(decode_block_kernel, cudaFuncAttributeMaxDynamicSharedMemorySize, SMEM_BYTES);
    }
    Maps tm;
    make_map(enc, &tm.v, d_in[2], 64, (uint64_t)2 * NHEAD * SK * 2, 64, TILE_KEYS * 2, CU_TENSOR_MAP_SWIZZLE_128B);
    make_map(enc, &tm.wq, d_in[3], QCOLS, D_MODEL, 64, 128, CU_TENSOR_MAP_SWIZZLE_128B);
    make_map(enc, &tm.wo, d_in[4], D_MODEL, QCOLS, 64, 128, CU_TENSOR_MAP_SWIZZLE_128B);
    make_map(enc, &tm.w1, d_in[6], FF, D_MODEL, 32, 256, CU_TENSOR_MAP_SWIZZLE_64B);
    make_map(enc, &tm.w2, d_in[8], D_MODEL, FF, 64, 32, CU_TENSOR_MAP_SWIZZLE_128B);
    decode_block_kernel<<<NCTA, NTHREADS, SMEM_BYTES>>>(
        tm, (const __nv_bfloat16*)d_in[0], (const __nv_bfloat16*)d_in[1], (const __nv_bfloat16*)d_in[7],
        (const __nv_bfloat16*)d_in[9], (__nv_bfloat16*)d_out, scr);
}
```

```cpp
#include <cuda_runtime.h>
#include <cuda_bf16.h>
#include <cuda.h>
#include <stdint.h>

namespace {

constexpr int D_MODEL = 512;
constexpr int NHEAD = 32;
constexpr int SK = 8192;
constexpr int DH = 128;
constexpr int FF = 1376;
constexpr int QCOLS = NHEAD * DH;

constexpr int NCTA = 128;
constexpr int KEYS_PER_CTA = SK / 2;
constexpr int TILE_KEYS = 64;
constexpr int TILE_BYTES = TILE_KEYS * DH * 2;
constexpr int NTILE = KEYS_PER_CTA / TILE_KEYS;
#define NST_ 12
#define NINIT_ 4
#define PACE_ 960
#define LEAD_ 7
#define WLATE_ 2
#define TD1_ 480
#define DLY2_ 300
constexpr int NST = NST_;
constexpr int NINIT = NINIT_;
constexpr int WLATE = WLATE_;
constexpr int LEAD = LEAD_;
constexpr int PACE = PACE_;
constexpr int SUMS_NS = TD1_;
constexpr int DELAY2 = DLY2_;
constexpr int NCONS = 256;
constexpr int NTHREADS = NCONS + 64;
constexpr int NMLP = FF / 32;
constexpr int KPRE = NST - 4;
constexpr int T_WQ = 0, T_K0 = 4, T_WO = T_K0 + KPRE, T_K1 = T_WO + 4, T_V = T_K1 + NTILE - KPRE, T_W1 = T_V + NTILE,
              T_W2 = T_W1 + 2, T_END = T_W2 + 2;

constexpr int OFF_RING = 0;
constexpr int OFF_SP = OFF_RING + NST * TILE_BYTES;
constexpr int OFF_PART = OFF_SP + KEYS_PER_CTA * 2;
constexpr int OFF_CS = OFF_PART + 8 * 64 * 4;
constexpr int OFF_XN = OFF_CS + 8 * 64 * 4;
constexpr int OFF_X = OFF_XN + 1024;
constexpr int O_STRIDE = 272;
constexpr int OFF_O = OFF_X + 2048 + 1024 + 64;
constexpr int OFF_Q = OFF_O + 4 * O_STRIDE;
constexpr int OFF_RED = OFF_Q + 256;
constexpr int OFF_STAT = OFF_RED + 64;
constexpr int OFF_HID = OFF_STAT + 128;
constexpr int OFF_ML = OFF_HID + 160;
constexpr int OFF_BAR = OFF_ML + 16;
constexpr int SMEM_USED = OFF_BAR + (2 * NST + 5) * 8;
constexpr int SMEM_BYTES = SMEM_USED + 1024;

constexpr float FX_SCALE = 1073741824.0f;
constexpr float FX_INV = 1.0f / 1073741824.0f;

constexpr int NFIN = 32;
struct Scratch {
    unsigned long long acc1[2 * D_MODEL];
    unsigned int tick[8 * 32];
    uint4 part[NFIN * NMLP * 8];
};
__device__ __align__(1024) Scratch g_scratch;

#define TSTAMP(i)

__device__ __forceinline__ void mbar_init(uint32_t bar, uint32_t cnt) {
    asm volatile("mbarrier.init.shared::cta.b64 [%0], %1;" ::"r"(bar), "r"(cnt) : "memory");
}
__device__ __forceinline__ void mbar_expect_tx(uint32_t bar, uint32_t bytes) {
    asm volatile("mbarrier.arrive.expect_tx.shared::cta.b64 _, [%0], %1;" ::"r"(bar), "r"(bytes) : "memory");
}
__device__ __forceinline__ void mbar_arrive(uint32_t bar) {
    asm volatile("mbarrier.arrive.shared::cta.b64 _, [%0];" ::"r"(bar) : "memory");
}
__device__ __forceinline__ bool mbar_test(uint32_t bar, uint32_t parity) {
    uint32_t ok;
    asm volatile("{\n.reg .pred p;\nmbarrier.test_wait.parity.shared::cta.b64 p, [%1], %2;\nselp.u32 %0, 1, 0, p;\n}"
                 : "=r"(ok) : "r"(bar), "r"(parity) : "memory");
    return ok;
}
__device__ __forceinline__ bool mbar_try(uint32_t bar, uint32_t parity) {
    uint32_t ok;
    asm volatile("{\n.reg .pred p;\nmbarrier.try_wait.parity.shared::cta.b64 p, [%1], %2;\nselp.u32 %0, 1, 0, p;\n}"
                 : "=r"(ok) : "r"(bar), "r"(parity) : "memory");
    return ok;
}
constexpr int SPIN_LIMIT = 1 << 20;
__device__ __forceinline__ void mbar_wait(uint32_t bar, uint32_t parity) {
    int n = 0;
    while (!mbar_try(bar, parity)) { if (++n > SPIN_LIMIT) __trap(); }
}
__device__ __forceinline__ void bulk_load(uint32_t dst, const void* src, uint32_t bytes, uint32_t bar) {
    asm volatile("cp.async.bulk.shared::cluster.global.mbarrier::complete_tx::bytes [%0], [%1], %2, [%3];"
                 ::"r"(dst), "l"(src), "r"(bytes), "r"(bar) : "memory");
}
__device__ __forceinline__ void tma2d(uint32_t dst, const CUtensorMap* tm, int c0, int c1, uint32_t bar) {
    asm volatile("cp.async.bulk.tensor.2d.shared::cluster.global.mbarrier::complete_tx::bytes [%0], [%1, {%3, %4}], [%2];"
                 ::"r"(dst), "l"(tm), "r"(bar), "r"(c0), "r"(c1) : "memory");
}
__device__ __forceinline__ void bulk_load_stream(uint32_t dst, const void* src, uint32_t bytes, uint32_t bar, uint64_t pol) {
    asm volatile("cp.async.bulk.shared::cluster.global.mbarrier::complete_tx::bytes.L2::cache_hint [%0], [%1], %2, [%3], %4;"
                 ::"r"(dst), "l"(src), "r"(bytes), "r"(bar), "l"(pol) : "memory");
}
__device__ __forceinline__ void tma2d_stream(uint32_t dst, const CUtensorMap* tm, int c0, int c1, uint32_t bar, uint64_t pol) {
    asm volatile("cp.async.bulk.tensor.2d.shared::cluster.global.mbarrier::complete_tx::bytes.L2::cache_hint [%0], [%1, {%3, %4}], [%2], %5;"
                 ::"r"(dst), "l"(tm), "r"(bar), "r"(c0), "r"(c1), "l"(pol) : "memory");
}
__device__ __forceinline__ bool elect_one() {
    uint32_t p;
    asm volatile("{\n.reg .pred p;\nelect.sync _|p, 0xffffffff;\nselp.u32 %0, 1, 0, p;\n}" : "=r"(p));
    return p;
}
__device__ __forceinline__ void cons_sync() { asm volatile("bar.sync 1, 256;" ::: "memory"); }

__device__ __forceinline__ uint32_t mapa(uint32_t addr, uint32_t rank) {
    uint32_t r;
    asm("mapa.shared::cluster.u32 %0, %1, %2;" : "=r"(r) : "r"(addr), "r"(rank));
    return r;
}
__device__ __forceinline__ void st_async_b32(uint32_t addr, uint32_t v, uint32_t bar) {
    asm volatile("st.async.weak.shared::cluster.mbarrier::complete_tx::bytes.b32 [%0], %1, [%2];" ::"r"(addr), "r"(v), "r"(bar) : "memory");
}
__device__ __forceinline__ void st_async_v2(uint32_t addr, uint32_t v0, uint32_t v1, uint32_t bar) {
    asm volatile("st.async.weak.shared::cluster.mbarrier::complete_tx::bytes.v2.b32 [%0], {%1, %2}, [%3];" ::"r"(addr), "r"(v0), "r"(v1), "r"(bar) : "memory");
}

__device__ __forceinline__ void mma_bf16(float (&d)[4], uint32_t a0, uint32_t a1, uint32_t a2, uint32_t a3, uint32_t b0, uint32_t b1) {
    asm volatile("mma.sync.aligned.m16n8k16.row.col.f32.bf16.bf16.f32 {%0,%1,%2,%3}, {%4,%5,%6,%7}, {%8,%9}, {%0,%1,%2,%3};"
                 : "+f"(d[0]), "+f"(d[1]), "+f"(d[2]), "+f"(d[3])
                 : "r"(a0), "r"(a1), "r"(a2), "r"(a3), "r"(b0), "r"(b1));
}
__device__ __forceinline__ void ldsm4(uint32_t (&r)[4], uint32_t addr) {
    asm volatile("ldmatrix.sync.aligned.m8n8.x4.shared.b16 {%0,%1,%2,%3}, [%4];"
                 : "=r"(r[0]), "=r"(r[1]), "=r"(r[2]), "=r"(r[3]) : "r"(addr) : "memory");
}
__device__ __forceinline__ void ldsm4t(uint32_t (&r)[4], uint32_t addr) {
    asm volatile("ldmatrix.sync.aligned.m8n8.x4.trans.shared.b16 {%0,%1,%2,%3}, [%4];"
                 : "=r"(r[0]), "=r"(r[1]), "=r"(r[2]), "=r"(r[3]) : "r"(addr) : "memory");
}
__device__ __forceinline__ uint4 lds128(uint32_t a) {
    uint4 v;
    asm volatile("ld.shared.v4.u32 {%0,%1,%2,%3}, [%4];" : "=r"(v.x), "=r"(v.y), "=r"(v.z), "=r"(v.w) : "r"(a) : "memory");
    return v;
}
__device__ __forceinline__ uint2 lds64(uint32_t a) {
    uint2 v;
    asm volatile("ld.shared.v2.u32 {%0,%1}, [%2];" : "=r"(v.x), "=r"(v.y) : "r"(a) : "memory");
    return v;
}
__device__ __forceinline__ uint32_t lds32(uint32_t a) {
    uint32_t v;
    asm volatile("ld.shared.u32 %0, [%1];" : "=r"(v) : "r"(a) : "memory");
    return v;
}
__device__ __forceinline__ void sts128(uint32_t a, uint4 v) {
    asm volatile("st.shared.v4.u32 [%0], {%1,%2,%3,%4};" ::"r"(a), "r"(v.x), "r"(v.y), "r"(v.z), "r"(v.w) : "memory");
}
__device__ __forceinline__ void sts64(uint32_t a, uint32_t v0, uint32_t v1) {
    asm volatile("st.shared.v2.u32 [%0], {%1,%2};" ::"r"(a), "r"(v0), "r"(v1) : "memory");
}
__device__ __forceinline__ void sts32(uint32_t a, uint32_t v) {
    asm volatile("st.shared.u32 [%0], %1;" ::"r"(a), "r"(v) : "memory");
}
__device__ __forceinline__ void sts16(uint32_t a, uint16_t v) {
    asm volatile("st.shared.u16 [%0], %1;" ::"r"(a), "h"(v) : "memory");
}
__device__ __forceinline__ float bf_lo(uint32_t v) { return __uint_as_float(v << 16); }
__device__ __forceinline__ float bf_hi(uint32_t v) { return __uint_as_float(v & 0xffff0000u); }
__device__ __forceinline__ uint32_t pack_bf(float lo, float hi) {
    uint32_t r;
    asm("cvt.rn.bf16x2.f32 %0, %1, %2;" : "=r"(r) : "f"(hi), "f"(lo));
    return r;
}
__device__ __forceinline__ float rnd_bf(float v) { return bf_lo(pack_bf(v, 0.f)); }

__device__ __forceinline__ unsigned long long fx_encode(float v) {
    return ((unsigned long long)__float2ll_rn(v * FX_SCALE) << 8) + 1ull;
}
__device__ __forceinline__ float fx_decode(uint32_t lo, uint32_t hi) {
    return fmaf(__int2float_rn((int)hi), 1.0f / 64.0f, __uint2float_rn(lo & 0xffffff00u) * (FX_INV / 256.0f));
}
__device__ __forceinline__ uint32_t gtime32() {
    uint32_t t;
    asm volatile("mov.u32 %0, %%globaltimer_lo;" : "=r"(t));
    return t;
}
__device__ __forceinline__ void wait_until(uint32_t t0, uint32_t ns) {
    for (int n = 0; gtime32() - t0 < ns && n < SPIN_LIMIT; n++) {}
}
__device__ __forceinline__ void spin_cycles(uint32_t n) {
    uint32_t t0, t;
    asm volatile("mov.u32 %0, %%clock;" : "=r"(t0));
    do { asm volatile("mov.u32 %0, %%clock;" : "=r"(t)); } while (t - t0 < n);
}
__device__ __forceinline__ void red_add64(unsigned long long* p, unsigned long long v) {
    asm volatile("red.relaxed.gpu.global.add.u64 [%0], %1;" ::"l"(p), "l"(v) : "memory");
}
__device__ __forceinline__ void ld_relaxed2x64(uint4& v, const void* p) {
    asm volatile("{\n.reg .b64 a, b;\nld.relaxed.gpu.global.v2.b64 {a, b}, [%4];\nmov.b64 {%0, %1}, a;\nmov.b64 {%2, %3}, b;\n}"
                 : "=r"(v.x), "=r"(v.y), "=r"(v.z), "=r"(v.w) : "l"(p) : "memory");
}
__device__ __forceinline__ void ld_relaxed128(uint4& v, const uint4* p) {
    asm volatile("ld.relaxed.gpu.global.v4.u32 {%0,%1,%2,%3}, [%4];" : "=r"(v.x), "=r"(v.y), "=r"(v.z), "=r"(v.w) : "l"(p) : "memory");
}
__device__ __forceinline__ uint32_t and3(uint32_t a, uint32_t b, uint32_t c) {
    uint32_t r;
    asm("lop3.b32 %0, %1, %2, %3, 0x80;" : "=r"(r) : "r"(a), "r"(b), "r"(c));
    return r;
}
__device__ __forceinline__ bool all_marked(const uint4& a, const uint4& b) {
    return __all_sync(~0u, and3(and3(a.x, a.y, a.z), and3(a.w, b.x, b.y), and3(b.z, b.w, 1u)));
}
__device__ __forceinline__ bool all_complete(const uint4& a, const uint4& b) {
    return __all_sync(~0u, and3(and3(a.x, a.z, b.x), b.z, 32u));
}
__device__ __forceinline__ float bf16_at(uint32_t a) {
    uint16_t v;
    asm volatile("ld.shared.u16 %0, [%1];" : "=h"(v) : "r"(a) : "memory");
    return __uint_as_float((uint32_t)v << 16);
}

__device__ __forceinline__ int bpos(int k) { return ((k >> 1) & 3) * 16 + ((k >> 4) & 3) * 4 + ((k >> 3) & 1) * 2 + (k & 1); }

__device__ __forceinline__ void gemv1_partial(const uint32_t* a1, uint32_t hb0, uint32_t hb1, int j, int c, uint32_t a) {
    float t0[4] = {0.f, 0.f, 0.f, 0.f}, t1[4] = {0.f, 0.f, 0.f, 0.f}, t2[4] = {0.f, 0.f, 0.f, 0.f}, t3[4] = {0.f, 0.f, 0.f, 0.f};
#pragma unroll
    for (int k = 0; k < 2; k++) {
        const uint32_t m0 = (j == k) ? hb0 : 0u, m1 = (j == k) ? hb1 : 0u;
        const uint32_t n0 = (j == k + 2) ? hb0 : 0u, n1 = (j == k + 2) ? hb1 : 0u;
        mma_bf16(t0, a1[8 * k], a1[8 * k + 1], a1[8 * k + 2], a1[8 * k + 3], m0, m1);
        mma_bf16(t1, a1[8 * k + 4], a1[8 * k + 5], a1[8 * k + 6], a1[8 * k + 7], m0, m1);
        mma_bf16(t2, a1[8 * k + 16], a1[8 * k + 17], a1[8 * k + 18], a1[8 * k + 19], n0, n1);
        mma_bf16(t3, a1[8 * k + 20], a1[8 * k + 21], a1[8 * k + 22], a1[8 * k + 23], n0, n1);
    }
    const bool up2 = c & 2, up1 = c & 1;
    float r4[4], r2[2];
    const float send[4] = {up2 ? t2[0] : t0[1], up2 ? t2[2] : t0[3], up2 ? t3[0] : t1[1], up2 ? t3[2] : t1[3]};
    const float keep[4] = {up2 ? t2[1] : t0[0], up2 ? t2[3] : t0[2], up2 ? t3[1] : t1[0], up2 ? t3[3] : t1[2]};
#pragma unroll
    for (int i = 0; i < 4; i++) r4[i] = keep[i] + __shfl_xor_sync(~0u, send[i], 2);
#pragma unroll
    for (int i = 0; i < 2; i++) r2[i] = (up1 ? r4[i + 2] : r4[i]) + __shfl_xor_sync(~0u, up1 ? r4[i] : r4[i + 2], 1);
    sts32(a, __float_as_uint(r2[0]));
    sts32(a + 32, __float_as_uint(r2[1]));
}

__device__ __forceinline__ float sum8(uint32_t a) {
    float p[8];
#pragma unroll
    for (int w = 0; w < 8; w++) p[w] = __uint_as_float(lds32(a + w * 256));
    return ((p[0] + p[1]) + (p[2] + p[3])) + ((p[4] + p[5]) + (p[6] + p[7]));
}

struct Maps { CUtensorMap v, wq, wo, w1, w2; };

__global__ void __cluster_dims__(2, 1, 1) __launch_bounds__(NTHREADS, 1)
decode_block_kernel(const __grid_constant__ Maps tm,
                    const __nv_bfloat16* __restrict__ x, const __nv_bfloat16* __restrict__ Kc,
                    const __nv_bfloat16* __restrict__ b1, const __nv_bfloat16* __restrict__ b2,
                    __nv_bfloat16* __restrict__ out, Scratch* __restrict__ scr, uint32_t tile_ns_x16) {
    unsigned long long* const g_acc1 = scr->acc1;
    unsigned int* const g_tick = scr->tick;
    uint4* const g_part = scr->part;
    extern __shared__ unsigned char smem_raw[];
    const uint32_t sb = ((uint32_t)__cvta_generic_to_shared(smem_raw) + 1023u) & ~1023u;
    const uint32_t bar_full = sb + OFF_BAR, bar_empty = bar_full + NST * 8;
    const uint32_t bar_q = bar_empty + NST * 8, bar_ml = bar_q + 8, bar_o = bar_ml + 8, bar_end = bar_o + 8, bar_go = bar_end + 8;

    TSTAMP(0);
    int tid = threadIdx.x;
    asm volatile("" : "+r"(tid));
    const int lane = tid & 31;
    const int warp = __shfl_sync(~0u, tid >> 5, 0);
    const int bh = blockIdx.x >> 1, rank = blockIdx.x & 1;
    const int b = bh >> 5, h = bh & 31;
    const bool is_mlp = (rank == 0) && (bh < NMLP);
    const int f0 = bh * 32;

    const char* ksrc = (const char*)Kc + (size_t)blockIdx.x * (KEYS_PER_CTA * DH * 2);
    constexpr uint64_t pol = 0x12F0000000000000ull;
    if (elect_one()) {
        if (warp < 6) {
            const int s = warp < 2 ? T_K0 + warp : warp - 2;
            const uint32_t fb = bar_full + s * 8;
            mbar_init(fb, 1);
            asm volatile("fence.mbarrier_init.release.cluster;" ::: "memory");
            mbar_expect_tx(fb, TILE_BYTES);
            if (warp < 2) bulk_load_stream(sb + OFF_RING + s * TILE_BYTES, ksrc + (size_t)warp * TILE_BYTES, TILE_BYTES, fb, pol);
            else tma2d(sb + OFF_RING + s * TILE_BYTES, &tm.wq, h * DH + rank * 64, s * 128, fb);
        } else if (warp == 7) {
#pragma unroll
            for (int s = 0; s < NST; s++) mbar_init(bar_empty + s * 8, 8);
            asm volatile("fence.mbarrier_init.release.cluster;" ::: "memory");
        } else if (warp == 8) {
#pragma unroll
            for (int s = T_K0 + 2; s < NST; s++) mbar_init(bar_full + s * 8, 1);
            asm volatile("fence.mbarrier_init.release.cluster;" ::: "memory");
#pragma unroll
            for (int s = T_K0 + 2; s < T_K0 + NINIT; s++) {
                mbar_expect_tx(bar_full + s * 8, TILE_BYTES);
                bulk_load_stream(sb + OFF_RING + s * TILE_BYTES, ksrc + (size_t)(s - T_K0) * TILE_BYTES, TILE_BYTES, bar_full + s * 8, pol);
            }
        } else if (warp == 9) {
            mbar_init(bar_q, 2); mbar_init(bar_ml, 1); mbar_init(bar_o, 10); mbar_init(bar_end, 1); mbar_init(bar_go, 1);
            asm volatile("fence.mbarrier_init.release.cluster;" ::: "memory");
            mbar_expect_tx(bar_q, 128);
            mbar_expect_tx(bar_ml, is_mlp ? 8 + 2048 + 1024 + 64 : 8);
            if (is_mlp) {
                bulk_load(sb + OFF_X, x, 2048, bar_ml);
                bulk_load(sb + OFF_X + 2048, b2, 1024, bar_ml);
                bulk_load(sb + OFF_X + 3072, b1 + f0, 64, bar_ml);
            }
            mbar_expect_tx(bar_o, 512);
            asm volatile("prefetch.tensormap [%0];" ::"l"(&tm.wo) : "memory");
            asm volatile("prefetch.tensormap [%0];" ::"l"(&tm.v) : "memory");
            asm volatile("prefetch.tensormap [%0];" ::"l"(&tm.w1) : "memory");
            asm volatile("prefetch.tensormap [%0];" ::"l"(&tm.w2) : "memory");
        }
    }
    __syncwarp();
    asm volatile("barrier.cluster.arrive.relaxed.aligned;" ::: "memory");

    if (warp == 8) {
        const uint32_t t_start = gtime32();
        asm volatile("barrier.cluster.wait.aligned;" ::: "memory");
        if (lane == 0) {
#pragma unroll
            for (int w = 0; w < 4; w++) mbar_wait(bar_full + (T_WQ + w) * 8, 0);
#pragma unroll
            for (int k = NINIT; k < KPRE; k++) {
                const uint32_t fb = bar_full + (T_K0 + k) * 8;
                mbar_expect_tx(fb, TILE_BYTES);
                bulk_load_stream(sb + OFF_RING + (T_K0 + k) * TILE_BYTES, ksrc + (size_t)k * TILE_BYTES, TILE_BYTES, fb, pol);
            }
            const int vline0 = (bh * SK + rank * KEYS_PER_CTA) * 2;
            const int tend = is_mlp ? T_END : T_W1;
            int st = 0, ph = 0;
#pragma unroll 1
            for (int t = NST; t < tend; t++) {
                const uint32_t dst = sb + OFF_RING + st * TILE_BYTES, fb = bar_full + st * 8;
                mbar_wait(bar_empty + st * 8, ph);
                wait_until(t_start, ((t - LEAD) * tile_ns_x16) >> 4);
                if (t == T_W1) {
                    mbar_wait(bar_full + ((T_W1 - 1 - WLATE) % NST) * 8, ((T_W1 - 1 - WLATE) / NST) & 1);
                }
                mbar_expect_tx(fb, TILE_BYTES);
                if (t < T_K1) {
                    tma2d(dst, &tm.wo, rank * 256 + (t - T_WO) * 64, h * DH, fb);
                } else if (t < T_V) {
                    bulk_load_stream(dst, ksrc + (size_t)(t - 8) * TILE_BYTES, TILE_BYTES, fb, pol);
                } else if (t < T_W1) {
                    tma2d_stream(dst, &tm.v, 0, vline0 + (t - T_V) * (TILE_KEYS * 2), fb, pol);
                } else if (t < T_W2) {
                    tma2d(dst, &tm.w1, f0, (t - T_W1) * 256, fb);
                } else {
#pragma unroll
                    for (int i = 0; i < 4; i++) tma2d(dst + i * 4096, &tm.w2, ((t - T_W2) * 4 + i) * 64, f0, fb);
                }
                if (++st == NST) { st = 0; ph ^= 1; }
            }
        }
        return;
    }

    if (warp == 9) {
        if (is_mlp) {
#pragma unroll
            for (int i = 0; i < 8; i++) g_part[((i * 4 + (lane >> 3)) * NMLP + bh) * 8 + (lane & 7)] = make_uint4(0, 0, 0, 0);
            __threadfence();
        }
        asm volatile("barrier.cluster.wait.aligned;" ::: "memory");
        if (lane == 0) mbar_arrive(bar_o);
        if (is_mlp) {
            mbar_wait(bar_end, 0);
            uint32_t cnt, tmax;
            int n = 0;
            do {
                uint2 v = make_uint2(0, 0);
                if (lane < 8) asm volatile("ld.relaxed.gpu.global.v2.u32 {%0, %1}, [%2];" : "=r"(v.x), "=r"(v.y) : "l"(g_tick + lane * 32) : "memory");
                cnt = __reduce_add_sync(~0u, v.x);
                tmax = __reduce_max_sync(~0u, v.y);
                if (++n > SPIN_LIMIT) __trap();
            } while (cnt < (unsigned)NCTA);
            wait_until(tmax, SUMS_NS);
            if (lane == 0) mbar_arrive(bar_go);
        }
        return;
    }

    const int g = lane >> 2, c = lane & 3;
    const int rr = lane & 7, mi = lane >> 3;
    const int mb_ = g & 1, j4 = g >> 1;
    const int d0 = warp * 64 + j4 * 16 + c * 2;
    uint32_t qa[16], wf[64];
    {
        if (warp == 6) {
            const uint4 xa0 = __ldg((const uint4*)(x + b * D_MODEL) + lane), xa1 = __ldg((const uint4*)(x + b * D_MODEL) + 32 + lane);
            const uint32_t xa[8] = {xa0.x, xa0.y, xa0.z, xa0.w, xa1.x, xa1.y, xa1.z, xa1.w};
            float s = 0.f;
#pragma unroll
            for (int i = 0; i < 8; i++) s += bf_lo(xa[i]) + bf_hi(xa[i]);
#pragma unroll
            for (int o = 16; o; o >>= 1) s += __shfl_xor_sync(~0u, s, o);
            const float mean = s * (1.0f / D_MODEL);
            float v = 0.f;
#pragma unroll
            for (int i = 0; i < 8; i++) { const float e0 = bf_lo(xa[i]) - mean, e1 = bf_hi(xa[i]) - mean; v += e0 * e0 + e1 * e1; }
#pragma unroll
            for (int o = 16; o; o >>= 1) v += __shfl_xor_sync(~0u, v, o);
            const float mb = rnd_bf(mean);
            const float den = rnd_bf(sqrtf(rnd_bf(rnd_bf(v * (1.0f / D_MODEL)) + 1e-5f)));
#pragma unroll
            for (int i = 0; i < 8; i++) {
                const int k = (i >> 2) * 256 + lane * 8 + (i & 3) * 2;
                sts32(sb + OFF_XN + ((k & ~63) + bpos(k)) * 2,
                      pack_bf(__fdiv_rn(rnd_bf(bf_lo(xa[i]) - mb), den), __fdiv_rn(rnd_bf(bf_hi(xa[i]) - mb), den)));
            }
        }
        asm volatile("barrier.cluster.wait.aligned;" ::: "memory");
        TSTAMP(12);
        cons_sync();

        float q0[4] = {0.f, 0.f, 0.f, 0.f}, q1[4] = {0.f, 0.f, 0.f, 0.f};
        const uint32_t aoff = ((warp >> 2) * 64 + (mi >> 1) * 8 + rr) * 128 + (((warp & 3) * 2 + (mi & 1)) ^ rr) * 16;
#pragma unroll
        for (int t = 0; t < 4; t++) {
            const uint32_t xaddr = sb + OFF_XN + (t * 2 + (warp >> 2)) * 128 + c * 32;
            const uint4 p0 = lds128(xaddr), p1 = lds128(xaddr + 16);
            const uint32_t base = sb + OFF_RING + (T_WQ + t) * TILE_BYTES + aoff;
            mbar_wait(bar_full + (T_WQ + t) * 8, 0);
            uint32_t a0[4], a1[4], a2[4], a3[4];
            ldsm4t(a0, base); ldsm4t(a1, base + 2048); ldsm4t(a2, base + 4096); ldsm4t(a3, base + 6144);
            mma_bf16(q0, a0[0], a0[1], a0[2], a0[3], p0.x, p0.y);
            mma_bf16(q1, a1[0], a1[1], a1[2], a1[3], p0.z, p0.w);
            mma_bf16(q0, a2[0], a2[1], a2[2], a2[3], p1.x, p1.y);
            mma_bf16(q1, a3[0], a3[1], a3[2], a3[3], p1.z, p1.w);
            __syncwarp();
            if (lane == 0) mbar_arrive(bar_empty + (T_WQ + t) * 8);
        }
        TSTAMP(13);
        if (c < 2) sts32(sb + OFF_PART + (warp * 16 + c * 8 + g) * 4, __float_as_uint(c ? q0[2] + q1[2] : q0[0] + q1[0]));
        cons_sync();
        if (warp == 0) {
            const uint2 u = lds64(sb + OFF_PART + lane * 8), w = lds64(sb + OFF_PART + 256 + lane * 8);
            const uint32_t qq = pack_bf(__uint_as_float(u.x) + __uint_as_float(w.x), __uint_as_float(u.y) + __uint_as_float(w.y));
            const uint32_t dst = sb + OFF_Q + rank * 128 + lane * 4;
            sts32(dst, qq);
            st_async_b32(mapa(dst, rank ^ 1), qq, mapa(bar_q, rank ^ 1));
            __syncwarp();
            if (lane == 0) mbar_arrive(bar_q);
        }
        mbar_wait(bar_q, 0);
#pragma unroll
        for (int j = 0; j < 16; j++) qa[j] = lds32(sb + OFF_Q + ((j & 8) + ((g + j) & 7)) * 16 + c * 4);
    }
    TSTAMP(1);

    int st = T_K0, ph = 0;
    float mx = -INFINITY;
    {
        uint32_t koff0 = sb + OFF_RING + (warp * 8 + rr) * 256 + ((rr + mi) & 7) * 16;
        uint32_t koff1 = sb + OFF_RING + (warp * 8 + rr) * 256 + ((rr + mi + 4) & 7) * 16;
        asm volatile("" : "+r"(koff0), "+r"(koff1));
        const bool valid = (c == (g >> 1));
        uint32_t spos = sb + OFF_SP + bpos(warp * 8 + g) * 2;
        auto k_tiles = [&](int n) {
#pragma unroll 1
            for (int i = 0; i < n; i++) {
                const uint32_t base = st * TILE_BYTES;
                mbar_wait(bar_full + st * 8, ph);
                uint32_t k0[4], k1[4], k2[4], k3[4];
                ldsm4(k0, base + koff0); ldsm4(k1, base + koff1);
                ldsm4(k2, base + koff0 + 128); ldsm4(k3, base + koff1 + 128);
                float s0[4] = {0.f, 0.f, 0.f, 0.f}, s1[4] = {0.f, 0.f, 0.f, 0.f};
                mma_bf16(s0, qa[0], qa[2], qa[1], qa[3], k0[0], k0[1]);
                mma_bf16(s1, qa[0], qa[2], qa[1], qa[3], k0[2], k0[3]);
                mma_bf16(s0, qa[4], qa[6], qa[5], qa[7], k1[0], k1[1]);
                mma_bf16(s1, qa[4], qa[6], qa[5], qa[7], k1[2], k1[3]);
                mma_bf16(s0, qa[8], qa[10], qa[9], qa[11], k2[0], k2[1]);
                mma_bf16(s1, qa[8], qa[10], qa[9], qa[11], k2[2], k2[3]);
                mma_bf16(s0, qa[12], qa[14], qa[13], qa[15], k3[0], k3[1]);
                mma_bf16(s1, qa[12], qa[14], qa[13], qa[15], k3[2], k3[3]);
                __syncwarp();
                if (lane == 0) mbar_arrive(bar_empty + st * 8);
                const float raw = (g & 1) ? s0[1] + s1[3] : s0[0] + s1[2];
                const uint32_t sc = pack_bf(rnd_bf(raw) * 0.08838834764831845f, 0.f);
                if (valid) { sts16(spos, (uint16_t)sc); mx = fmaxf(mx, bf_lo(sc)); }
                spos += TILE_KEYS * 2;
                if (++st == NST) { st = 0; ph ^= 1; }
            }
        };
        k_tiles(KPRE);
        {
            static_assert(T_WO == NST, "wo tiles sit in slots 0..3, second pass");
            const int s = warp >> 1;
            const int row = (mi >> 1) * 4 + (rr >> 1) + (rr & 1) * 8;
            const uint32_t base = sb + OFF_RING + s * TILE_BYTES + row * 128;
            const uint32_t c0 = (((mi & 1) * 2 + (warp & 1)) ^ (row & 7)) * 16, c1 = c0 ^ 64;
            mbar_wait(bar_full + s * 8, 1);
#pragma unroll
            for (int t = 0; t < 8; t++) {
                ldsm4t(*(uint32_t(*)[4])(wf + 8 * t), base + t * 2048 + c0);
                ldsm4t(*(uint32_t(*)[4])(wf + 8 * t + 4), base + t * 2048 + c1);
            }
            __syncwarp();
            if (lane < 4) mbar_arrive(bar_empty + lane * 8);
            st = 4;
        }
        k_tiles(NTILE - KPRE);
    }
    TSTAMP(2);
    {
#pragma unroll
        for (int o = 16; o; o >>= 1) mx = fmaxf(mx, __shfl_xor_sync(~0u, mx, o));
        if (lane == 0) sts32(sb + OFF_RED + warp * 4, __float_as_uint(mx));
        cons_sync();
        const uint4 m0 = lds128(sb + OFF_RED), m1 = lds128(sb + OFF_RED + 16);
        const float mloc = fmaxf(fmaxf(fmaxf(__uint_as_float(m0.x), __uint_as_float(m0.y)), fmaxf(__uint_as_float(m0.z), __uint_as_float(m0.w))),
                                 fmaxf(fmaxf(__uint_as_float(m1.x), __uint_as_float(m1.y)), fmaxf(__uint_as_float(m1.z), __uint_as_float(m1.w))));
        const uint4 s0 = lds128(sb + OFF_SP + tid * 16), s1 = lds128(sb + OFF_SP + 4096 + tid * 16);
        const uint32_t sv[8] = {s0.x, s0.y, s0.z, s0.w, s1.x, s1.y, s1.z, s1.w};
        constexpr float LOG2E = 1.4426950408889634f;
        float l = 0.f;
#pragma unroll
        for (int i = 0; i < 8; i++) l += exp2f((bf_lo(sv[i]) - mloc) * LOG2E) + exp2f((bf_hi(sv[i]) - mloc) * LOG2E);
#pragma unroll
        for (int o = 16; o; o >>= 1) l += __shfl_xor_sync(~0u, l, o);
        if (lane == 0) sts32(sb + OFF_RED + 32 + warp * 4, __float_as_uint(l));
        cons_sync();
        const uint4 l0 = lds128(sb + OFF_RED + 32), l1 = lds128(sb + OFF_RED + 48);
        const float lloc = ((__uint_as_float(l0.x) + __uint_as_float(l0.y)) + (__uint_as_float(l0.z) + __uint_as_float(l0.w))) +
                           ((__uint_as_float(l1.x) + __uint_as_float(l1.y)) + (__uint_as_float(l1.z) + __uint_as_float(l1.w)));
        if (tid == 0) st_async_v2(mapa(sb + OFF_ML, rank ^ 1), __float_as_uint(mloc), __float_as_uint(lloc), mapa(bar_ml, rank ^ 1));
        mbar_wait(bar_ml, 0);
        const uint2 pml = lds64(sb + OFF_ML);
        const float mp = __uint_as_float(pml.x), lp = __uint_as_float(pml.y);
        const float M = fmaxf(mloc, mp);
        const float m_a = rank ? mp : mloc, l_a = rank ? lp : lloc, m_b = rank ? mloc : mp, l_b = rank ? lloc : lp;
        const float L = l_a * exp2f((m_a - M) * LOG2E) + l_b * exp2f((m_b - M) * LOG2E);
        const float inv = 1.0f / L;
        uint32_t pv[8];
#pragma unroll
        for (int i = 0; i < 8; i++)
            pv[i] = pack_bf(exp2f((bf_lo(sv[i]) - M) * LOG2E) * inv, exp2f((bf_hi(sv[i]) - M) * LOG2E) * inv);
        sts128(sb + OFF_SP + tid * 16, make_uint4(pv[0], pv[1], pv[2], pv[3]));
        sts128(sb + OFF_SP + 4096 + tid * 16, make_uint4(pv[4], pv[5], pv[6], pv[7]));
        cons_sync();
    }
    TSTAMP(3);
    unsigned long long* acc1_dst = g_acc1 + b * D_MODEL + rank * 256 + warp * 32 + c * 8 + g;
    uint32_t o_dst = sb + OFF_O + (rank * 2 + (c & 1)) * O_STRIDE + (warp * 8 + g) * 4, o_bar = bar_o;
    if (c & 2) { o_dst = mapa(o_dst, rank ^ 1); o_bar = mapa(bar_o, rank ^ 1); }
    uint32_t o_src = sb + OFF_O + (rr & 3) * O_STRIDE + mi * 16;
    unsigned* tick_dst = g_tick + (bh & 7) * 32;
    asm volatile("" : "+l"(acc1_dst), "+l"(tick_dst), "+r"(o_dst), "+r"(o_bar), "+r"(o_src));
    const bool is_fin = bh < NFIN;
    const unsigned long long* p1 = g_acc1 + mb_ * D_MODEL + warp * 64 + j4 * 8 + c * 2;
    uint4* part_dst = g_part + ((warp * 4 + c) * NMLP + bh) * 8 + g;
    const uint4* inbox = g_part + bh * (NMLP * 8) + tid;
    const uint4* inbox2 = tid < (NMLP - 32) * 8 ? inbox + 256 : inbox;
    const uint4* inbox_pf = g_part + (bh * NMLP + tid) * 8;
    int do_pf = is_fin && tid < NMLP;
    float wsel = tid < (NMLP - 32) * 8 ? 1.0f : 0.0f;
    __nv_bfloat16* out_dst = out + ((lane >> 3) & 1) * D_MODEL + bh * 16 + (lane >> 4) * 8 + (lane & 7);
    asm volatile("" : "+l"(p1), "+l"(part_dst), "+l"(inbox), "+l"(inbox2), "+l"(inbox_pf), "+r"(do_pf), "+f"(wsel), "+l"(out_dst));
    uint32_t xv[2] = {lds32(sb + OFF_X + (mb_ * D_MODEL + d0) * 2), lds32(sb + OFF_X + (mb_ * D_MODEL + d0 + 8) * 2)};
    float b1v = bf16_at(sb + OFF_X + 3072 + lane * 2);
    float b2v = bf16_at(sb + OFF_X + 2048 + ((bh & 31) * 16 + (lane >> 4) * 8 + (lane & 7)) * 2);
    uint32_t a_part = sb + OFF_PART + warp * 256 + ((c >> 1) * 32 + (c & 1) * 16 + g) * 4;
    uint32_t a_stat = sb + OFF_STAT + (mb_ * 16 + (c & 1) * 8 + warp) * 4;
    uint32_t a_keep = sb + OFF_RED + mb_ * 32 + c * 4;
    uint32_t a_sum = sb + OFF_PART + (warp * 32 + lane) * 4, a_cs = sb + OFF_CS + lane * 4;
    uint32_t a_hid = sb + OFF_HID + warp * 80 + lane * 2, a_hidb = sb + OFF_HID + (rr & 1) * 80 + mi * 16;
    uint32_t a_fin = sb + OFF_PART + warp * 256 + lane * 4;
    uint32_t a_hfin = sb + OFF_RED + ((lane >> 3) & 1) * 32 + ((lane >> 4) * 8 + (lane & 7)) * 2;
    int keep_h = warp * 4 + j4 == bh;
    asm volatile("" : "+r"(a_part), "+r"(a_stat), "+r"(a_keep), "+r"(a_sum), "+r"(a_cs), "+r"(a_hid), "+r"(a_hidb), "+r"(a_fin), "+r"(a_hfin),
                 "+r"(keep_h), "+f"(b1v), "+f"(b2v));
    static_assert(T_W1 % NST + 3 < NST, "w1/w2 occupy four consecutive slots with the same parity");
    constexpr int W_PAR = (T_W1 / NST) & 1;
    uint32_t w1_bar = bar_full + (T_W1 % NST + (warp >> 2)) * 8;
    uint32_t w1_a = sb + OFF_RING + (T_W1 % NST + (warp >> 2)) * TILE_BYTES + ((warp & 3) * 64 + (mi >> 1) * 8 + rr) * 64 + ((mi & 1) ^ (rr >> 1)) * 16;
    uint32_t w2_a = sb + OFF_RING + (T_W2 % NST + (warp >> 2)) * TILE_BYTES + (warp & 3) * 4096 + ((mi >> 1) * 8 + rr) * 128 + ((mi & 1) ^ rr) * 16;
    asm volatile("" : "+r"(w1_bar), "+r"(w1_a), "+r"(w2_a));
    {
        const int hh = warp >> 2, ch = 2 * (warp & 3);
        const int line = 2 * (8 * (mi >> 1) + rr) + hh;
        uint32_t voff = sb + OFF_RING + line * 128 + (((ch ^ (mi & 1) ^ (rr >> 2)) ^ (line & 7)) * 16);
        uint32_t pmask = ((c >> 1) == (g & 1)) ? 0xffffffffu : 0u;
        asm volatile("" : "+r"(voff), "+r"(pmask));
        uint32_t paddr = sb + OFF_SP + c * 32;
        float o0[4] = {0.f, 0.f, 0.f, 0.f}, o1[4] = {0.f, 0.f, 0.f, 0.f};
#pragma unroll 1
        for (int i = 0; i < NTILE; i++) {
            const uint32_t base = voff + st * TILE_BYTES;
            uint4 p0 = lds128(paddr), p1 = lds128(paddr + 16);
            p0.x &= pmask; p0.y &= pmask; p0.z &= pmask; p0.w &= pmask;
            p1.x &= pmask; p1.y &= pmask; p1.z &= pmask; p1.w &= pmask;
            asm volatile("" : "+r"(p0.x), "+r"(p0.y), "+r"(p0.z), "+r"(p0.w), "+r"(p1.x), "+r"(p1.y), "+r"(p1.z), "+r"(p1.w));
            mbar_wait(bar_full + st * 8, ph);
            uint32_t a0[4], a1[4], a2[4], a3[4];
            ldsm4t(a0, base); ldsm4t(a1, base + 4096); ldsm4t(a2, base + 8192); ldsm4t(a3, base + 12288);
            if (i == NTILE - 1 && tid == 0) {
                asm volatile("red.relaxed.gpu.global.max.u32 [%0], %1;" ::"l"(tick_dst + 1), "r"(gtime32()) : "memory");
                asm volatile("red.relaxed.gpu.global.add.u32 [%0], 1;" ::"l"(tick_dst) : "memory");
                mbar_arrive(bar_end);
            }
            mma_bf16(o0, a0[0], a0[1], a0[2], a0[3], p0.x, p0.y);
            mma_bf16(o1, a1[0], a1[1], a1[2], a1[3], p0.z, p0.w);
            mma_bf16(o0, a2[0], a2[1], a2[2], a2[3], p1.x, p1.y);
            mma_bf16(o1, a3[0], a3[1], a3[2], a3[3], p1.z, p1.w);
            __syncwarp();
            if (lane == 0) mbar_arrive(bar_empty + st * 8);
            paddr += TILE_KEYS * 2;
            if (++st == NST) { st = 0; ph ^= 1; }
        }
        TSTAMP(4);
        const float v0 = (o0[0] + o1[0]) + (o0[3] + o1[3]);
        const float v1 = (o0[1] + o1[1]) + (o0[2] + o1[2]);
        const uint32_t hi = pack_bf(v0, v1);
        const uint32_t val = (c & 1) ? pack_bf(v0 - bf_lo(hi), v1 - bf_hi(hi)) : hi;
        if (c & 2) st_async_b32(o_dst, val, o_bar);
        else sts32(o_dst, val);
        __syncwarp();
        if (lane == 0) mbar_arrive(bar_o);
        mbar_wait(bar_o, 0);
    }
    TSTAMP(5);
    {
        float d00[4] = {0.f, 0.f, 0.f, 0.f}, d01[4] = {0.f, 0.f, 0.f, 0.f}, d10[4] = {0.f, 0.f, 0.f, 0.f}, d11[4] = {0.f, 0.f, 0.f, 0.f};
        uint32_t ob[4][4];
#pragma unroll
        for (int t = 0; t < 4; t++) ldsm4(ob[t], o_src + t * 64);
#pragma unroll
        for (int t = 0; t < 4; t++) {
            mma_bf16(d00, wf[16 * t], wf[16 * t + 1], wf[16 * t + 2], wf[16 * t + 3], ob[t][0], ob[t][1]);
            mma_bf16(d10, wf[16 * t + 4], wf[16 * t + 5], wf[16 * t + 6], wf[16 * t + 7], ob[t][0], ob[t][1]);
            mma_bf16(d01, wf[16 * t + 8], wf[16 * t + 9], wf[16 * t + 10], wf[16 * t + 11], ob[t][2], ob[t][3]);
            mma_bf16(d11, wf[16 * t + 12], wf[16 * t + 13], wf[16 * t + 14], wf[16 * t + 15], ob[t][2], ob[t][3]);
        }
        const float e0 = (d00[0] + d01[0]) + (d00[1] + d01[1]), e1 = (d00[2] + d01[2]) + (d00[3] + d01[3]);
        const float e2 = (d10[0] + d11[0]) + (d10[1] + d11[1]), e3 = (d10[2] + d11[2]) + (d10[3] + d11[3]);
        const float ea = (c & 2) ? e2 : e0, eb = (c & 2) ? e3 : e1;
        const float e = ((c & 1) ? eb : ea) + __shfl_xor_sync(~0u, (c & 1) ? ea : eb, 1);
        red_add64(acc1_dst, fx_encode(e));
    }
    TSTAMP(6);
    if (!is_mlp) return;

    {
        if (do_pf) asm volatile("prefetch.global.L2 [%0];" ::"l"(inbox_pf));
        uint32_t* a1 = wf;
        uint32_t* a2 = wf + 32;
        auto load_w1 = [&]() {
#pragma unroll
            for (int k = 0; k < 4; k++) {
                ldsm4t(*(uint32_t(*)[4])(a1 + 8 * k), w1_a + k * 1024);
                ldsm4t(*(uint32_t(*)[4])(a1 + 8 * k + 4), (w1_a ^ 32) + k * 1024);
            }
            gemv1_partial(a1, 0x3f803f80u, 0x3f803f80u, j4, c, a_part + (OFF_CS - OFF_PART));
        };
        auto load_w2 = [&]() {
#pragma unroll
            for (int u = 0; u < 2; u++)
#pragma unroll
                for (int T = 0; T < 4; T++) ldsm4t(*(uint32_t(*)[4])(a2 + 16 * u + 4 * T), (w2_a ^ (T * 32)) + u * 2048);
        };
        uint32_t hb0, hb1;
        {
            uint4 ua = make_uint4(0, 0, 0, 0), ub = ua;
            int n = 0, stage = 0, polled = 0;
#pragma unroll 1
            do {
                if (!polled && __all_sync(~0u, mbar_test(bar_go, 0))) {
                    TSTAMP(7);
                    ld_relaxed2x64(ua, p1); ld_relaxed2x64(ub, p1 + 32);
                    polled = 1;
                }
                if (stage < 2 && __all_sync(~0u, mbar_test(w1_bar + stage * 16, W_PAR))) {
                    if (stage == 0) load_w1(); else load_w2();
                    stage++;
                }
                if (++n > SPIN_LIMIT * 16) __trap();
            } while (stage < 2 || !polled);
            n = 0;
            while (!all_complete(ua, ub)) {
                ld_relaxed2x64(ua, p1); ld_relaxed2x64(ub, p1 + 32);
                if (++n > SPIN_LIMIT) __trap();
            }
            const uint32_t at0 = pack_bf(fx_decode(ua.x, ua.y), fx_decode(ua.z, ua.w)), at1 = pack_bf(fx_decode(ub.x, ub.y), fx_decode(ub.z, ub.w));
            hb0 = pack_bf(bf_lo(xv[0]) + bf_lo(at0), bf_hi(xv[0]) + bf_hi(at0));
            hb1 = pack_bf(bf_lo(xv[1]) + bf_lo(at1), bf_hi(xv[1]) + bf_hi(at1));
        }
        TSTAMP(8);
        gemv1_partial(a1, hb0, hb1, j4, c, a_part);
        {
            const float h0 = bf_lo(hb0), h1 = bf_hi(hb0), h2 = bf_lo(hb1), h3 = bf_hi(hb1);
            const float s1 = (h0 + h1) + (h2 + h3);
            const float s2 = (h0 * h0 + h1 * h1) + (h2 * h2 + h3 * h3);
            float t = ((c & 1) ? s2 : s1) + __shfl_xor_sync(~0u, (c & 1) ? s1 : s2, 1);
            t += __shfl_xor_sync(~0u, t, 2);
            t += __shfl_xor_sync(~0u, t, 8);
            t += __shfl_xor_sync(~0u, t, 16);
            if ((lane & 0x1a) == 0) sts32(a_stat, __float_as_uint(t));
        }
        if (keep_h) {
            sts32(a_keep, hb0);
            sts32(a_keep + 16, hb1);
        }
        cons_sync();
        TSTAMP(9);
        if (warp < 2) {
            const uint4 q0 = lds128(sb + OFF_STAT + warp * 64), q1 = lds128(sb + OFF_STAT + warp * 64 + 16);
            const uint4 q2 = lds128(sb + OFF_STAT + warp * 64 + 32), q3 = lds128(sb + OFF_STAT + warp * 64 + 48);
            const float sacc = sum8(a_sum);
            const float cs = sum8(a_cs);
            const float mean = (((__uint_as_float(q0.x) + __uint_as_float(q0.y)) + (__uint_as_float(q0.z) + __uint_as_float(q0.w))) +
                                ((__uint_as_float(q1.x) + __uint_as_float(q1.y)) + (__uint_as_float(q1.z) + __uint_as_float(q1.w)))) * (1.0f / D_MODEL);
            const float msq = (((__uint_as_float(q2.x) + __uint_as_float(q2.y)) + (__uint_as_float(q2.z) + __uint_as_float(q2.w))) +
                               ((__uint_as_float(q3.x) + __uint_as_float(q3.y)) + (__uint_as_float(q3.z) + __uint_as_float(q3.w)))) * (1.0f / D_MODEL);
            const float var = fmaxf(msq - mean * mean, 0.f);
            float sq, iden;
            asm("sqrt.approx.ftz.f32 %0, %1;" : "=f"(sq) : "f"(rnd_bf(rnd_bf(var) + 1e-5f)));
            asm("rcp.approx.ftz.f32 %0, %1;" : "=f"(iden) : "f"(rnd_bf(sq)));
            const float z = fmaxf(rnd_bf(rnd_bf((sacc - rnd_bf(mean) * cs) * iden) + b1v), 0.f);
            sts16(a_hid, (uint16_t)pack_bf(z * z, 0.f));
        }
        cons_sync();
        uint32_t hb[4];
        ldsm4(hb, a_hidb);
        const float hfin = bf16_at(a_hfin);
        float y[4][4];
#pragma unroll
        for (int T = 0; T < 4; T++) {
            y[T][0] = y[T][1] = y[T][2] = y[T][3] = 0.f;
            mma_bf16(y[T], a2[4 * T], a2[4 * T + 1], a2[4 * T + 2], a2[4 * T + 3], hb[0], hb[1]);
        }
#pragma unroll
        for (int T = 0; T < 4; T++)
            mma_bf16(y[T], a2[16 + 4 * T], a2[16 + 4 * T + 1], a2[16 + 4 * T + 2], a2[16 + 4 * T + 3], hb[2], hb[3]);
        {
            const bool up2 = c & 2, up1 = c & 1;
            uint32_t e[4];
#pragma unroll
            for (int i = 0; i < 4; i++) e[i] = __float_as_uint(up2 ? (up1 ? y[3][i] : y[2][i]) : (up1 ? y[1][i] : y[0][i])) | 1u;
            asm volatile("st.relaxed.gpu.global.v4.u32 [%0], {%1,%2,%3,%4};" ::"l"(part_dst), "r"(e[0]), "r"(e[1]), "r"(e[2]), "r"(e[3]) : "memory");
        }
        TSTAMP(10);
        if (!is_fin) return;
        {
            uint4 u, w;
            int n = 0;
            spin_cycles(DELAY2);
            do {
                ld_relaxed128(u, inbox); ld_relaxed128(w, inbox2);
                if (++n > SPIN_LIMIT) __trap();
            } while (!all_marked(u, w));
            const float v0 = fmaf(__uint_as_float(w.x), wsel, __uint_as_float(u.x)), v1 = fmaf(__uint_as_float(w.y), wsel, __uint_as_float(u.y));
            const float v2 = fmaf(__uint_as_float(w.z), wsel, __uint_as_float(u.z)), v3 = fmaf(__uint_as_float(w.w), wsel, __uint_as_float(u.w));
            const bool up16 = lane & 16, up8 = lane & 8;
            const float r0 = (up16 ? v2 : v0) + __shfl_xor_sync(~0u, up16 ? v0 : v2, 16);
            const float r1 = (up16 ? v3 : v1) + __shfl_xor_sync(~0u, up16 ? v1 : v3, 16);
            const float r = (up8 ? r1 : r0) + __shfl_xor_sync(~0u, up8 ? r0 : r1, 8);
            sts32(a_fin, __float_as_uint(r));
        }
        cons_sync();
        if (warp == 0) {
            const float y2 = sum8(a_sum);
            *out_dst = __ushort_as_bfloat16((unsigned short)pack_bf(hfin + rnd_bf(rnd_bf(y2) + b2v), 0.f));
        }
        if (bh == 0) {
            *(ulonglong2*)(g_acc1 + tid * 4) = make_ulonglong2(0, 0);
            *(ulonglong2*)(g_acc1 + tid * 4 + 2) = make_ulonglong2(0, 0);
            g_tick[tid] = 0;
        }
        TSTAMP(11);
    }
}

typedef CUresult (*EncodeFn)(CUtensorMap*, CUtensorMapDataType, cuuint32_t, void*, const cuuint64_t*, const cuuint64_t*,
                             const cuuint32_t*, const cuuint32_t*, CUtensorMapInterleave, CUtensorMapSwizzle,
                             CUtensorMapL2promotion, CUtensorMapFloatOOBfill);

void make_map(EncodeFn enc, CUtensorMap* tm, void* ptr, uint64_t cols, uint64_t rows, uint32_t box_cols, uint32_t box_rows,
              CUtensorMapSwizzle swz) {
    const cuuint64_t dims[2] = {cols, rows};
    const cuuint64_t strides[1] = {cols * 2};
    const cuuint32_t box[2] = {box_cols, box_rows};
    const cuuint32_t es[2] = {1, 1};
    enc(tm, CU_TENSOR_MAP_DATA_TYPE_BFLOAT16, 2, ptr, dims, strides, box, es, CU_TENSOR_MAP_INTERLEAVE_NONE, swz,
        CU_TENSOR_MAP_L2_PROMOTION_NONE, CU_TENSOR_MAP_FLOAT_OOB_FILL_NONE);
}

}

extern "C" void kernel_launch(void* const* d_in, const int* in_sizes, int n_in, void* d_out, int out_size) {
    (void)in_sizes; (void)n_in; (void)out_size;
    static EncodeFn enc = nullptr;
    static Scratch* scr = nullptr;
    static uint32_t tile_ns_x16 = 0;
    if (!enc) {
        void* fn = nullptr;
        cudaDriverEntryPointQueryResult qr;
        cudaGetDriverEntryPoint("cuTensorMapEncodeTiled", &fn, cudaEnableDefault, &qr);
        enc = (EncodeFn)fn;
        cudaGetSymbolAddress((void**)&scr, g_scratch);
        int dev = 0, mem_khz = 0, bus_bits = 0;
        cudaGetDevice(&dev);
        cudaDeviceGetAttribute(&mem_khz, cudaDevAttrMemoryClockRate, dev);
        cudaDeviceGetAttribute(&bus_bits, cudaDevAttrGlobalMemoryBusWidth, dev);
        const double bytes_per_ns = 2.0 * mem_khz * 1e-6 * (bus_bits / 8) * (PACE * 1e-3);
        if (bytes_per_ns > 0) tile_ns_x16 = (uint32_t)(16.0 * NCTA * TILE_BYTES / bytes_per_ns);
        cudaFuncSetAttribute(decode_block_kernel, cudaFuncAttributeMaxDynamicSharedMemorySize, SMEM_BYTES);
    }
    Maps tm;
    make_map(enc, &tm.v, d_in[2], 64, (uint64_t)2 * NHEAD * SK * 2, 64, TILE_KEYS * 2, CU_TENSOR_MAP_SWIZZLE_128B);
    make_map(enc, &tm.wq, d_in[3], QCOLS, D_MODEL, 64, 128, CU_TENSOR_MAP_SWIZZLE_128B);
    make_map(enc, &tm.wo, d_in[4], D_MODEL, QCOLS, 64, 128, CU_TENSOR_MAP_SWIZZLE_128B);
    make_map(enc, &tm.w1, d_in[6], FF, D_MODEL, 32, 256, CU_TENSOR_MAP_SWIZZLE_64B);
    make_map(enc, &tm.w2, d_in[8], D_MODEL, FF, 64, 32, CU_TENSOR_MAP_SWIZZLE_128B);
    decode_block_kernel<<<NCTA, NTHREADS, SMEM_BYTES>>>(
        tm, (const __nv_bfloat16*)d_in[0], (const __nv_bfloat16*)d_in[1], (const __nv_bfloat16*)d_in[7],
        (const __nv_bfloat16*)d_in[9], (__nv_bfloat16*)d_out, scr, tile_ns_x16);
}
```

```cpp
#include <cuda_runtime.h>
#include <cuda_bf16.h>
#include <cuda.h>
#include <stdint.h>

namespace {

constexpr int D_MODEL = 512;
constexpr int NHEAD = 32;
constexpr int SK = 8192;
constexpr int DH = 128;
constexpr int FF = 1376;
constexpr int QCOLS = NHEAD * DH;

constexpr int NCTA = 128;
constexpr int KEYS_PER_CTA = SK / 2;
constexpr int TILE_KEYS = 64;
constexpr int TILE_BYTES = TILE_KEYS * DH * 2;
constexpr int NTILE = KEYS_PER_CTA / TILE_KEYS;
constexpr int NST = 12;
constexpr int NINIT = 4;
constexpr int WLATE = 1;
constexpr int LEAD = 7;
constexpr int PACE = 958;
constexpr int SKEW = 10;
constexpr int DELAY2 = 300;
constexpr int NCONS = 256;
constexpr int NTHREADS = NCONS + 64;
constexpr int NMLP = FF / 32;
constexpr int KPRE = NST - 4;
constexpr int T_WQ = 0, T_K0 = 4, T_WO = T_K0 + KPRE, T_K1 = T_WO + 4, T_V = T_K1 + NTILE - KPRE, T_W1 = T_V + NTILE,
              T_W2 = T_W1 + 2, T_END = T_W2 + 2;

constexpr int OFF_RING = 0;
constexpr int OFF_SP = OFF_RING + NST * TILE_BYTES;
constexpr int OFF_PART = OFF_SP + KEYS_PER_CTA * 2;
constexpr int OFF_CS = OFF_PART + 8 * 64 * 4;
constexpr int OFF_XN = OFF_CS + 32 * 4;
constexpr int OFF_X = OFF_XN + 1024;
constexpr int O_STRIDE = 272;
constexpr int OFF_O = OFF_X + 2048 + 1024 + 64;
constexpr int OFF_Q = OFF_O + 4 * O_STRIDE;
constexpr int OFF_RED = OFF_Q + 256;
constexpr int OFF_STAT = OFF_RED + 64;
constexpr int OFF_HID = OFF_STAT + 128;
constexpr int OFF_ML = OFF_HID + 160;
constexpr int OFF_BAR = OFF_ML + 16;
constexpr int SMEM_USED = OFF_BAR + (2 * NST + 5) * 8;
constexpr int SMEM_BYTES = SMEM_USED + 1024;

constexpr float FX_SCALE = 1073741824.0f;
constexpr float FX_INV = 1.0f / 1073741824.0f;

constexpr int NFIN = 32;
struct Scratch {
    unsigned long long acc1[2 * D_MODEL];
    unsigned int tick[8 * 32];
    uint4 part[NFIN * NMLP * 8];
};
__device__ __align__(1024) Scratch g_scratch;

__device__ __forceinline__ void mbar_init(uint32_t bar, uint32_t cnt) {
    asm volatile("mbarrier.init.shared::cta.b64 [%0], %1;" ::"r"(bar), "r"(cnt) : "memory");
}
__device__ __forceinline__ void mbar_expect_tx(uint32_t bar, uint32_t bytes) {
    asm volatile("mbarrier.arrive.expect_tx.shared::cta.b64 _, [%0], %1;" ::"r"(bar), "r"(bytes) : "memory");
}
__device__ __forceinline__ void mbar_arrive(uint32_t bar) {
    asm volatile("mbarrier.arrive.shared::cta.b64 _, [%0];" ::"r"(bar) : "memory");
}
__device__ __forceinline__ bool mbar_test(uint32_t bar, uint32_t parity) {
    uint32_t ok;
    asm volatile("{\n.reg .pred p;\nmbarrier.test_wait.parity.shared::cta.b64 p, [%1], %2;\nselp.u32 %0, 1, 0, p;\n}"
                 : "=r"(ok) : "r"(bar), "r"(parity) : "memory");
    return ok;
}
__device__ __forceinline__ bool mbar_try(uint32_t bar, uint32_t parity) {
    uint32_t ok;
    asm volatile("{\n.reg .pred p;\nmbarrier.try_wait.parity.shared::cta.b64 p, [%1], %2;\nselp.u32 %0, 1, 0, p;\n}"
                 : "=r"(ok) : "r"(bar), "r"(parity) : "memory");
    return ok;
}
constexpr int SPIN_LIMIT = 1 << 20;
__device__ __forceinline__ void mbar_wait(uint32_t bar, uint32_t parity) {
    int n = 0;
    while (!mbar_try(bar, parity)) { if (++n > SPIN_LIMIT) __trap(); }
}
__device__ __forceinline__ void bulk_load(uint32_t dst, const void* src, uint32_t bytes, uint32_t bar) {
    asm volatile("cp.async.bulk.shared::cluster.global.mbarrier::complete_tx::bytes [%0], [%1], %2, [%3];"
                 ::"r"(dst), "l"(src), "r"(bytes), "r"(bar) : "memory");
}
__device__ __forceinline__ void tma2d(uint32_t dst, const CUtensorMap* tm, int c0, int c1, uint32_t bar) {
    asm volatile("cp.async.bulk.tensor.2d.shared::cluster.global.mbarrier::complete_tx::bytes [%0], [%1, {%3, %4}], [%2];"
                 ::"r"(dst), "l"(tm), "r"(bar), "r"(c0), "r"(c1) : "memory");
}
__device__ __forceinline__ void bulk_load_stream(uint32_t dst, const void* src, uint32_t bytes, uint32_t bar, uint64_t pol) {
    asm volatile("cp.async.bulk.shared::cluster.global.mbarrier::complete_tx::bytes.L2::cache_hint [%0], [%1], %2, [%3], %4;"
                 ::"r"(dst), "l"(src), "r"(bytes), "r"(bar), "l"(pol) : "memory");
}
__device__ __forceinline__ void tma2d_stream(uint32_t dst, const CUtensorMap* tm, int c0, int c1, uint32_t bar, uint64_t pol) {
    asm volatile("cp.async.bulk.tensor.2d.shared::cluster.global.mbarrier::complete_tx::bytes.L2::cache_hint [%0], [%1, {%3, %4}], [%2], %5;"
                 ::"r"(dst), "l"(tm), "r"(bar), "r"(c0), "r"(c1), "l"(pol) : "memory");
}
__device__ __forceinline__ bool elect_one() {
    uint32_t p;
    asm volatile("{\n.reg .pred p;\nelect.sync _|p, 0xffffffff;\nselp.u32 %0, 1, 0, p;\n}" : "=r"(p));
    return p;
}
__device__ __forceinline__ void cons_sync() { asm volatile("bar.sync 1, 256;" ::: "memory"); }

__device__ __forceinline__ uint32_t mapa(uint32_t addr, uint32_t rank) {
    uint32_t r;
    asm("mapa.shared::cluster.u32 %0, %1, %2;" : "=r"(r) : "r"(addr), "r"(rank));
    return r;
}
__device__ __forceinline__ void st_async_b32(uint32_t addr, uint32_t v, uint32_t bar) {
    asm volatile("st.async.weak.shared::cluster.mbarrier::complete_tx::bytes.b32 [%0], %1, [%2];" ::"r"(addr), "r"(v), "r"(bar) : "memory");
}
__device__ __forceinline__ void st_async_v2(uint32_t addr, uint32_t v0, uint32_t v1, uint32_t bar) {
    asm volatile("st.async.weak.shared::cluster.mbarrier::complete_tx::bytes.v2.b32 [%0], {%1, %2}, [%3];" ::"r"(addr), "r"(v0), "r"(v1), "r"(bar) : "memory");
}

__device__ __forceinline__ void mma_bf16(float (&d)[4], uint32_t a0, uint32_t a1, uint32_t a2, uint32_t a3, uint32_t b0, uint32_t b1) {
    asm volatile("mma.sync.aligned.m16n8k16.row.col.f32.bf16.bf16.f32 {%0,%1,%2,%3}, {%4,%5,%6,%7}, {%8,%9}, {%0,%1,%2,%3};"
                 : "+f"(d[0]), "+f"(d[1]), "+f"(d[2]), "+f"(d[3])
                 : "r"(a0), "r"(a1), "r"(a2), "r"(a3), "r"(b0), "r"(b1));
}
__device__ __forceinline__ void ldsm4(uint32_t (&r)[4], uint32_t addr) {
    asm volatile("ldmatrix.sync.aligned.m8n8.x4.shared.b16 {%0,%1,%2,%3}, [%4];"
                 : "=r"(r[0]), "=r"(r[1]), "=r"(r[2]), "=r"(r[3]) : "r"(addr) : "memory");
}
__device__ __forceinline__ void ldsm4t(uint32_t (&r)[4], uint32_t addr) {
    asm volatile("ldmatrix.sync.aligned.m8n8.x4.trans.shared.b16 {%0,%1,%2,%3}, [%4];"
                 : "=r"(r[0]), "=r"(r[1]), "=r"(r[2]), "=r"(r[3]) : "r"(addr) : "memory");
}
__device__ __forceinline__ uint4 lds128(uint32_t a) {
    uint4 v;
    asm volatile("ld.shared.v4.u32 {%0,%1,%2,%3}, [%4];" : "=r"(v.x), "=r"(v.y), "=r"(v.z), "=r"(v.w) : "r"(a) : "memory");
    return v;
}
__device__ __forceinline__ uint2 lds64(uint32_t a) {
    uint2 v;
    asm volatile("ld.shared.v2.u32 {%0,%1}, [%2];" : "=r"(v.x), "=r"(v.y) : "r"(a) : "memory");
    return v;
}
__device__ __forceinline__ uint32_t lds32(uint32_t a) {
    uint32_t v;
    asm volatile("ld.shared.u32 %0, [%1];" : "=r"(v) : "r"(a) : "memory");
    return v;
}
__device__ __forceinline__ void sts128(uint32_t a, uint4 v) {
    asm volatile("st.shared.v4.u32 [%0], {%1,%2,%3,%4};" ::"r"(a), "r"(v.x), "r"(v.y), "r"(v.z), "r"(v.w) : "memory");
}
__device__ __forceinline__ void sts64(uint32_t a, uint32_t v0, uint32_t v1) {
    asm volatile("st.shared.v2.u32 [%0], {%1,%2};" ::"r"(a), "r"(v0), "r"(v1) : "memory");
}
__device__ __forceinline__ void sts32(uint32_t a, uint32_t v) {
    asm volatile("st.shared.u32 [%0], %1;" ::"r"(a), "r"(v) : "memory");
}
__device__ __forceinline__ void sts16(uint32_t a, uint16_t v) {
    asm volatile("st.shared.u16 [%0], %1;" ::"r"(a), "h"(v) : "memory");
}
__device__ __forceinline__ float bf_lo(uint32_t v) { return __uint_as_float(v << 16); }
__device__ __forceinline__ float bf_hi(uint32_t v) { return __uint_as_float(v & 0xffff0000u); }
__device__ __forceinline__ uint32_t pack_bf(float lo, float hi) {
    uint32_t r;
    asm("cvt.rn.bf16x2.f32 %0, %1, %2;" : "=r"(r) : "f"(hi), "f"(lo));
    return r;
}
__device__ __forceinline__ float rnd_bf(float v) { return bf_lo(pack_bf(v, 0.f)); }

__device__ __forceinline__ unsigned long long fx_encode(float v) {
    return ((unsigned long long)__float2ll_rn(v * FX_SCALE) << 8) + 1ull;
}
__device__ __forceinline__ float fx_decode(uint32_t lo, uint32_t hi) {
    return fmaf(__int2float_rn((int)hi), 1.0f / 64.0f, __uint2float_rn(lo & 0xffffff00u) * (FX_INV / 256.0f));
}
__device__ __forceinline__ uint32_t gtime32() {
    uint32_t t;
    asm volatile("mov.u32 %0, %%globaltimer_lo;" : "=r"(t));
    return t;
}
__device__ __forceinline__ void wait_until(uint32_t t0, uint32_t ns) {
    for (int n = 0; gtime32() - t0 < ns && n < SPIN_LIMIT; n++) {}
}
__device__ __forceinline__ void spin_cycles(uint32_t n) {
    uint32_t t0, t;
    asm volatile("mov.u32 %0, %%clock;" : "=r"(t0));
    do { asm volatile("mov.u32 %0, %%clock;" : "=r"(t)); } while (t - t0 < n);
}
__device__ __forceinline__ void red_add64(unsigned long long* p, unsigned long long v) {
    asm volatile("red.relaxed.gpu.global.add.u64 [%0], %1;" ::"l"(p), "l"(v) : "memory");
}
__device__ __forceinline__ void ld_relaxed2x64(uint4& v, const void* p) {
    asm volatile("{\n.reg .b64 a, b;\nld.relaxed.gpu.global.v2.b64 {a, b}, [%4];\nmov.b64 {%0, %1}, a;\nmov.b64 {%2, %3}, b;\n}"
                 : "=r"(v.x), "=r"(v.y), "=r"(v.z), "=r"(v.w) : "l"(p) : "memory");
}
__device__ __forceinline__ void ld_relaxed128(uint4& v, const uint4* p) {
    asm volatile("ld.relaxed.gpu.global.v4.u32 {%0,%1,%2,%3}, [%4];" : "=r"(v.x), "=r"(v.y), "=r"(v.z), "=r"(v.w) : "l"(p) : "memory");
}
__device__ __forceinline__ uint32_t and3(uint32_t a, uint32_t b, uint32_t c) {
    uint32_t r;
    asm("lop3.b32 %0, %1, %2, %3, 0x80;" : "=r"(r) : "r"(a), "r"(b), "r"(c));
    return r;
}
__device__ __forceinline__ bool all_marked(const uint4& a, const uint4& b) {
    return __all_sync(~0u, and3(and3(a.x, a.y, a.z), and3(a.w, b.x, b.y), and3(b.z, b.w, 1u)));
}
__device__ __forceinline__ bool all_complete(const uint4& a, const uint4& b) {
    return __all_sync(~0u, and3(and3(a.x, a.z, b.x), b.z, 32u));
}
__device__ __forceinline__ float bf16_at(uint32_t a) {
    uint16_t v;
    asm volatile("ld.shared.u16 %0, [%1];" : "=h"(v) : "r"(a) : "memory");
    return __uint_as_float((uint32_t)v << 16);
}

__device__ __forceinline__ int bpos(int k) { return ((k >> 1) & 3) * 16 + ((k >> 4) & 3) * 4 + ((k >> 3) & 1) * 2 + (k & 1); }

__device__ __forceinline__ void gemv1_partial(const uint32_t* a1, uint32_t hb0, uint32_t hb1, int j, int c, uint32_t a) {
    float t0[4] = {0.f, 0.f, 0.f, 0.f}, t1[4] = {0.f, 0.f, 0.f, 0.f}, t2[4] = {0.f, 0.f, 0.f, 0.f}, t3[4] = {0.f, 0.f, 0.f, 0.f};
#pragma unroll
    for (int k = 0; k < 2; k++) {
        const uint32_t m0 = (j == k) ? hb0 : 0u, m1 = (j == k) ? hb1 : 0u;
        const uint32_t n0 = (j == k + 2) ? hb0 : 0u, n1 = (j == k + 2) ? hb1 : 0u;
        mma_bf16(t0, a1[8 * k], a1[8 * k + 1], a1[8 * k + 2], a1[8 * k + 3], m0, m1);
        mma_bf16(t1, a1[8 * k + 4], a1[8 * k + 5], a1[8 * k + 6], a1[8 * k + 7], m0, m1);
        mma_bf16(t2, a1[8 * k + 16], a1[8 * k + 17], a1[8 * k + 18], a1[8 * k + 19], n0, n1);
        mma_bf16(t3, a1[8 * k + 20], a1[8 * k + 21], a1[8 * k + 22], a1[8 * k + 23], n0, n1);
    }
    const bool up2 = c & 2, up1 = c & 1;
    float r4[4], r2[2];
    const float send[4] = {up2 ? t2[0] : t0[1], up2 ? t2[2] : t0[3], up2 ? t3[0] : t1[1], up2 ? t3[2] : t1[3]};
    const float keep[4] = {up2 ? t2[1] : t0[0], up2 ? t2[3] : t0[2], up2 ? t3[1] : t1[0], up2 ? t3[3] : t1[2]};
#pragma unroll
    for (int i = 0; i < 4; i++) r4[i] = keep[i] + __shfl_xor_sync(~0u, send[i], 2);
#pragma unroll
    for (int i = 0; i < 2; i++) r2[i] = (up1 ? r4[i + 2] : r4[i]) + __shfl_xor_sync(~0u, up1 ? r4[i] : r4[i + 2], 1);
    sts32(a, __float_as_uint(r2[0]));
    sts32(a + 32, __float_as_uint(r2[1]));
}

__device__ __forceinline__ float sum8(uint32_t a) {
    float p[8];
#pragma unroll
    for (int w = 0; w < 8; w++) p[w] = __uint_as_float(lds32(a + w * 256));
    return ((p[0] + p[1]) + (p[2] + p[3])) + ((p[4] + p[5]) + (p[6] + p[7]));
}

struct Maps { CUtensorMap v, wq, wo, w1, w2; };

__global__ void __cluster_dims__(2, 1, 1) __launch_bounds__(NTHREADS, 1)
decode_block_kernel(const __grid_constant__ Maps tm,
                    const __nv_bfloat16* __restrict__ x, const __nv_bfloat16* __restrict__ Kc,
                    const __nv_bfloat16* __restrict__ b1, const __nv_bfloat16* __restrict__ b2,
                    __nv_bfloat16* __restrict__ out, Scratch* __restrict__ scr, uint32_t tile_ns_x16) {
    unsigned long long* const g_acc1 = scr->acc1;
    unsigned int* const g_tick = scr->tick;
    uint4* const g_part = scr->part;
    extern __shared__ unsigned char smem_raw[];
    const uint32_t sb = ((uint32_t)__cvta_generic_to_shared(smem_raw) + 1023u) & ~1023u;
    const uint32_t bar_full = sb + OFF_BAR, bar_empty = bar_full + NST * 8;
    const uint32_t bar_q = bar_empty + NST * 8, bar_ml = bar_q + 8, bar_o = bar_ml + 8, bar_end = bar_o + 8, bar_go = bar_end + 8;

    int tid = threadIdx.x;
    asm volatile("" : "+r"(tid));
    const int lane = tid & 31;
    const int warp = __shfl_sync(~0u, tid >> 5, 0);
    const int bh = blockIdx.x >> 1, rank = blockIdx.x & 1;
    const int b = bh >> 5, h = bh & 31;
    const bool is_mlp = (rank == 0) && (bh < NMLP);
    const int f0 = bh * 32;

    const char* ksrc = (const char*)Kc + (size_t)blockIdx.x * (KEYS_PER_CTA * DH * 2);
    constexpr uint64_t pol = 0x12F0000000000000ull;
    if (elect_one()) {
        if (warp < 6) {
            const int s = warp < 2 ? T_K0 + warp : warp - 2;
            const uint32_t fb = bar_full + s * 8;
            mbar_init(fb, 1);
            asm volatile("fence.mbarrier_init.release.cluster;" ::: "memory");
            mbar_expect_tx(fb, TILE_BYTES);
            if (warp < 2) bulk_load_stream(sb + OFF_RING + s * TILE_BYTES, ksrc + (size_t)warp * TILE_BYTES, TILE_BYTES, fb, pol);
            else tma2d(sb + OFF_RING + s * TILE_BYTES, &tm.wq, h * DH + rank * 64, s * 128, fb);
        } else if (warp == 7) {
#pragma unroll
            for (int s = 0; s < NST; s++) mbar_init(bar_empty + s * 8, 8);
            asm volatile("fence.mbarrier_init.release.cluster;" ::: "memory");
        } else if (warp == 8) {
#pragma unroll
            for (int s = T_K0 + 2; s < NST; s++) mbar_init(bar_full + s * 8, 1);
            asm volatile("fence.mbarrier_init.release.cluster;" ::: "memory");
#pragma unroll
            for (int s = T_K0 + 2; s < T_K0 + NINIT; s++) {
                mbar_expect_tx(bar_full + s * 8, TILE_BYTES);
                bulk_load_stream(sb + OFF_RING + s * TILE_BYTES, ksrc + (size_t)(s - T_K0) * TILE_BYTES, TILE_BYTES, bar_full + s * 8, pol);
            }
        } else if (warp == 9) {
            mbar_init(bar_q, 2); mbar_init(bar_ml, 1); mbar_init(bar_o, 10); mbar_init(bar_end, 1); mbar_init(bar_go, 1);
            asm volatile("fence.mbarrier_init.release.cluster;" ::: "memory");
            mbar_expect_tx(bar_q, 128);
            mbar_expect_tx(bar_ml, is_mlp ? 8 + 2048 + 1024 + 64 : 8);
            if (is_mlp) {
                bulk_load(sb + OFF_X, x, 2048, bar_ml);
                bulk_load(sb + OFF_X + 2048, b2, 1024, bar_ml);
                bulk_load(sb + OFF_X + 3072, b1 + f0, 64, bar_ml);
            }
            mbar_expect_tx(bar_o, 512);
            asm volatile("prefetch.tensormap [%0];" ::"l"(&tm.wo) : "memory");
            asm volatile("prefetch.tensormap [%0];" ::"l"(&tm.v) : "memory");
            asm volatile("prefetch.tensormap [%0];" ::"l"(&tm.w1) : "memory");
            asm volatile("prefetch.tensormap [%0];" ::"l"(&tm.w2) : "memory");
        }
    }
    __syncwarp();
    asm volatile("barrier.cluster.arrive.relaxed.aligned;" ::: "memory");

    if (warp == 8) {
        const uint32_t t_start = gtime32();
        asm volatile("barrier.cluster.wait.aligned;" ::: "memory");
        if (lane == 0) {
#pragma unroll
            for (int w = 0; w < 4; w++) mbar_wait(bar_full + (T_WQ + w) * 8, 0);
#pragma unroll
            for (int k = NINIT; k < KPRE; k++) {
                const uint32_t fb = bar_full + (T_K0 + k) * 8;
                mbar_expect_tx(fb, TILE_BYTES);
                bulk_load_stream(sb + OFF_RING + (T_K0 + k) * TILE_BYTES, ksrc + (size_t)k * TILE_BYTES, TILE_BYTES, fb, pol);
            }
            const int vline0 = (bh * SK + rank * KEYS_PER_CTA) * 2;
            const int tend = is_mlp ? T_END : T_W1;
            const int lead16 = LEAD * 16 + (bh < NMLP ? SKEW : -2 * SKEW);
            int st = 0, ph = 0;
#pragma unroll 1
            for (int t = NST; t < tend; t++) {
                const uint32_t dst = sb + OFF_RING + st * TILE_BYTES, fb = bar_full + st * 8;
                mbar_wait(bar_empty + st * 8, ph);
                wait_until(t_start, ((t * 16 - lead16) * tile_ns_x16) >> 8);
                if (t == T_W1) {
                    mbar_wait(bar_full + ((T_W1 - 1 - WLATE) % NST) * 8, ((T_W1 - 1 - WLATE) / NST) & 1);
                }
                mbar_expect_tx(fb, TILE_BYTES);
                if (t < T_K1) {
                    tma2d(dst, &tm.wo, rank * 256 + (t - T_WO) * 64, h * DH, fb);
                } else if (t < T_V) {
                    bulk_load_stream(dst, ksrc + (size_t)(t - 8) * TILE_BYTES, TILE_BYTES, fb, pol);
                } else if (t < T_W1) {
                    tma2d_stream(dst, &tm.v, 0, vline0 + (t - T_V) * (TILE_KEYS * 2), fb, pol);
                } else if (t < T_W2) {
                    tma2d(dst, &tm.w1, f0, (t - T_W1) * 256, fb);
                } else {
#pragma unroll
                    for (int i = 0; i < 4; i++) tma2d(dst + i * 4096, &tm.w2, ((t - T_W2) * 4 + i) * 64, f0, fb);
                }
                if (++st == NST) { st = 0; ph ^= 1; }
            }
        }
        if (is_mlp) {
            __syncwarp();
            const int rr = lane & 7, mi = lane >> 3;
            float cs[4][4];
#pragma unroll
            for (int i = 0; i < 4; i++) cs[i][0] = cs[i][1] = cs[i][2] = cs[i][3] = 0.f;
#pragma unroll
            for (int t = 0; t < 2; t++) {
                const uint32_t a = sb + OFF_RING + (T_W1 % NST + t) * TILE_BYTES + ((mi >> 1) * 8 + rr) * 64 + ((mi & 1) ^ (rr >> 1)) * 16;
                mbar_wait(bar_full + (T_W1 % NST + t) * 8, (T_W1 / NST) & 1);
#pragma unroll 4
                for (int k = 0; k < 16; k += 2) {
                    uint32_t w[4][4];
                    ldsm4t(w[0], a + k * 1024); ldsm4t(w[1], (a ^ 32) + k * 1024);
                    ldsm4t(w[2], a + k * 1024 + 1024); ldsm4t(w[3], (a ^ 32) + k * 1024 + 1024);
#pragma unroll
                    for (int i = 0; i < 4; i++) mma_bf16(cs[i], w[i][0], w[i][1], w[i][2], w[i][3], 0x3f803f80u, 0x3f803f80u);
                }
            }
            const int c = lane & 3;
            const float lo = (c & 1) ? cs[0][2] + cs[2][2] : cs[0][0] + cs[2][0], hi = (c & 1) ? cs[1][2] + cs[3][2] : cs[1][0] + cs[3][0];
            sts32(sb + OFF_CS + (c * 8 + (lane >> 2)) * 4, __float_as_uint((c & 2) ? hi : lo));
            asm volatile("bar.arrive 2, 288;" ::: "memory");
        }
        return;
    }

    if (warp == 9) {
        if (is_mlp) {
#pragma unroll
            for (int i = 0; i < 8; i++) g_part[((i * 4 + (lane >> 3)) * NMLP + bh) * 8 + (lane & 7)] = make_uint4(0, 0, 0, 0);
            __threadfence();
        }
        asm volatile("barrier.cluster.wait.aligned;" ::: "memory");
        if (lane == 0) mbar_arrive(bar_o);
        if (is_mlp) {
            mbar_wait(bar_end, 0);
            for (int n = 0;; n++) {
                unsigned v = 0;
                if (lane < 8) asm volatile("ld.relaxed.gpu.global.u32 %0, [%1];" : "=r"(v) : "l"(g_tick + lane * 32) : "memory");
                if (__reduce_add_sync(~0u, v) >= NCTA) break;
                if (n > SPIN_LIMIT) __trap();
            }
            if (lane == 0) mbar_arrive(bar_go);
        }
        return;
    }

    const int g = lane >> 2, c = lane & 3;
    const int rr = lane & 7, mi = lane >> 3;
    const int mb_ = g & 1, j4 = g >> 1;
    const int d0 = warp * 64 + j4 * 16 + c * 2;
    uint32_t qa[16], wf[64];
    {
        if (warp == 6) {
            const uint4 xa0 = __ldg((const uint4*)(x + b * D_MODEL) + lane), xa1 = __ldg((const uint4*)(x + b * D_MODEL) + 32 + lane);
            const uint32_t xa[8] = {xa0.x, xa0.y, xa0.z, xa0.w, xa1.x, xa1.y, xa1.z, xa1.w};
            float s = 0.f;
#pragma unroll
            for (int i = 0; i < 8; i++) s += bf_lo(xa[i]) + bf_hi(xa[i]);
#pragma unroll
            for (int o = 16; o; o >>= 1) s += __shfl_xor_sync(~0u, s, o);
            const float mean = s * (1.0f / D_MODEL);
            float v = 0.f;
#pragma unroll
            for (int i = 0; i < 8; i++) { const float e0 = bf_lo(xa[i]) - mean, e1 = bf_hi(xa[i]) - mean; v += e0 * e0 + e1 * e1; }
#pragma unroll
            for (int o = 16; o; o >>= 1) v += __shfl_xor_sync(~0u, v, o);
            const float mb = rnd_bf(mean);
            const float den = rnd_bf(sqrtf(rnd_bf(rnd_bf(v * (1.0f / D_MODEL)) + 1e-5f)));
#pragma unroll
            for (int i = 0; i < 8; i++) {
                const int k = (i >> 2) * 256 + lane * 8 + (i & 3) * 2;
                sts32(sb + OFF_XN + ((k & ~63) + bpos(k)) * 2,
                      pack_bf(__fdiv_rn(rnd_bf(bf_lo(xa[i]) - mb), den), __fdiv_rn(rnd_bf(bf_hi(xa[i]) - mb), den)));
            }
        }
        asm volatile("barrier.cluster.wait.aligned;" ::: "memory");
        cons_sync();

        float q0[4] = {0.f, 0.f, 0.f, 0.f}, q1[4] = {0.f, 0.f, 0.f, 0.f};
        const uint32_t aoff = ((warp >> 2) * 64 + (mi >> 1) * 8 + rr) * 128 + (((warp & 3) * 2 + (mi & 1)) ^ rr) * 16;
#pragma unroll
        for (int t = 0; t < 4; t++) {
            const uint32_t xaddr = sb + OFF_XN + (t * 2 + (warp >> 2)) * 128 + c * 32;
            const uint4 p0 = lds128(xaddr), p1 = lds128(xaddr + 16);
            const uint32_t base = sb + OFF_RING + (T_WQ + t) * TILE_BYTES + aoff;
            mbar_wait(bar_full + (T_WQ + t) * 8, 0);
            uint32_t a0[4], a1[4], a2[4], a3[4];
            ldsm4t(a0, base); ldsm4t(a1, base + 2048); ldsm4t(a2, base + 4096); ldsm4t(a3, base + 6144);
            mma_bf16(q0, a0[0], a0[1], a0[2], a0[3], p0.x, p0.y);
            mma_bf16(q1, a1[0], a1[1], a1[2], a1[3], p0.z, p0.w);
            mma_bf16(q0, a2[0], a2[1], a2[2], a2[3], p1.x, p1.y);
            mma_bf16(q1, a3[0], a3[1], a3[2], a3[3], p1.z, p1.w);
            __syncwarp();
            if (lane == 0) mbar_arrive(bar_empty + (T_WQ + t) * 8);
        }
        if (c < 2) sts32(sb + OFF_PART + (warp * 16 + c * 8 + g) * 4, __float_as_uint(c ? q0[2] + q1[2] : q0[0] + q1[0]));
        cons_sync();
        if (warp == 0) {
            const uint2 u = lds64(sb + OFF_PART + lane * 8), w = lds64(sb + OFF_PART + 256 + lane * 8);
            const uint32_t qq = pack_bf(__uint_as_float(u.x) + __uint_as_float(w.x), __uint_as_float(u.y) + __uint_as_float(w.y));
            const uint32_t dst = sb + OFF_Q + rank * 128 + lane * 4;
            sts32(dst, qq);
            st_async_b32(mapa(dst, rank ^ 1), qq, mapa(bar_q, rank ^ 1));
            __syncwarp();
            if (lane == 0) mbar_arrive(bar_q);
        }
        mbar_wait(bar_q, 0);
#pragma unroll
        for (int j = 0; j < 16; j++) qa[j] = lds32(sb + OFF_Q + ((j & 8) + ((g + j) & 7)) * 16 + c * 4);
    }

    int st = T_K0, ph = 0;
    float mx = -INFINITY;
    {
        uint32_t koff0 = sb + OFF_RING + (warp * 8 + rr) * 256 + ((rr + mi) & 7) * 16;
        uint32_t koff1 = sb + OFF_RING + (warp * 8 + rr) * 256 + ((rr + mi + 4) & 7) * 16;
        asm volatile("" : "+r"(koff0), "+r"(koff1));
        const bool valid = (c == (g >> 1));
        uint32_t spos = sb + OFF_SP + bpos(warp * 8 + g) * 2;
        auto k_tiles = [&](int n) {
#pragma unroll 1
            for (int i = 0; i < n; i++) {
                const uint32_t base = st * TILE_BYTES;
                mbar_wait(bar_full + st * 8, ph);
                uint32_t k0[4], k1[4], k2[4], k3[4];
                ldsm4(k0, base + koff0); ldsm4(k1, base + koff1);
                ldsm4(k2, base + koff0 + 128); ldsm4(k3, base + koff1 + 128);
                float s0[4] = {0.f, 0.f, 0.f, 0.f}, s1[4] = {0.f, 0.f, 0.f, 0.f};
                mma_bf16(s0, qa[0], qa[2], qa[1], qa[3], k0[0], k0[1]);
                mma_bf16(s1, qa[0], qa[2], qa[1], qa[3], k0[2], k0[3]);
                mma_bf16(s0, qa[4], qa[6], qa[5], qa[7], k1[0], k1[1]);
                mma_bf16(s1, qa[4], qa[6], qa[5], qa[7], k1[2], k1[3]);
                mma_bf16(s0, qa[8], qa[10], qa[9], qa[11], k2[0], k2[1]);
                mma_bf16(s1, qa[8], qa[10], qa[9], qa[11], k2[2], k2[3]);
                mma_bf16(s0, qa[12], qa[14], qa[13], qa[15], k3[0], k3[1]);
                mma_bf16(s1, qa[12], qa[14], qa[13], qa[15], k3[2], k3[3]);
                __syncwarp();
                if (lane == 0) mbar_arrive(bar_empty + st * 8);
                const float raw = (g & 1) ? s0[1] + s1[3] : s0[0] + s1[2];
                const uint32_t sc = pack_bf(rnd_bf(raw) * 0.08838834764831845f, 0.f);
                if (valid) { sts16(spos, (uint16_t)sc); mx = fmaxf(mx, bf_lo(sc)); }
                spos += TILE_KEYS * 2;
                if (++st == NST) { st = 0; ph ^= 1; }
            }
        };
        k_tiles(KPRE);
        {
            static_assert(T_WO == NST, "wo tiles sit in slots 0..3, second pass");
            const int s = warp >> 1;
            const int row = (mi >> 1) * 4 + (rr >> 1) + (rr & 1) * 8;
            const uint32_t base = sb + OFF_RING + s * TILE_BYTES + row * 128;
            const uint32_t c0 = (((mi & 1) * 2 + (warp & 1)) ^ (row & 7)) * 16, c1 = c0 ^ 64;
            mbar_wait(bar_full + s * 8, 1);
#pragma unroll
            for (int t = 0; t < 8; t++) {
                ldsm4t(*(uint32_t(*)[4])(wf + 8 * t), base + t * 2048 + c0);
                ldsm4t(*(uint32_t(*)[4])(wf + 8 * t + 4), base + t * 2048 + c1);
            }
            __syncwarp();
            if (lane < 4) mbar_arrive(bar_empty + lane * 8);
            st = 4;
        }
        k_tiles(NTILE - KPRE);
    }
    {
#pragma unroll
        for (int o = 16; o; o >>= 1) mx = fmaxf(mx, __shfl_xor_sync(~0u, mx, o));
        if (lane == 0) sts32(sb + OFF_RED + warp * 4, __float_as_uint(mx));
        cons_sync();
        const uint4 m0 = lds128(sb + OFF_RED), m1 = lds128(sb + OFF_RED + 16);
        const float mloc = fmaxf(fmaxf(fmaxf(__uint_as_float(m0.x), __uint_as_float(m0.y)), fmaxf(__uint_as_float(m0.z), __uint_as_float(m0.w))),
                                 fmaxf(fmaxf(__uint_as_float(m1.x), __uint_as_float(m1.y)), fmaxf(__uint_as_float(m1.z), __uint_as_float(m1.w))));
        const uint4 s0 = lds128(sb + OFF_SP + tid * 16), s1 = lds128(sb + OFF_SP + 4096 + tid * 16);
        const uint32_t sv[8] = {s0.x, s0.y, s0.z, s0.w, s1.x, s1.y, s1.z, s1.w};
        constexpr float LOG2E = 1.4426950408889634f;
        float l = 0.f;
#pragma unroll
        for (int i = 0; i < 8; i++) l += exp2f((bf_lo(sv[i]) - mloc) * LOG2E) + exp2f((bf_hi(sv[i]) - mloc) * LOG2E);
#pragma unroll
        for (int o = 16; o; o >>= 1) l += __shfl_xor_sync(~0u, l, o);
        if (lane == 0) sts32(sb + OFF_RED + 32 + warp * 4, __float_as_uint(l));
        cons_sync();
        const uint4 l0 = lds128(sb + OFF_RED + 32), l1 = lds128(sb + OFF_RED + 48);
        const float lloc = ((__uint_as_float(l0.x) + __uint_as_float(l0.y)) + (__uint_as_float(l0.z) + __uint_as_float(l0.w))) +
                           ((__uint_as_float(l1.x) + __uint_as_float(l1.y)) + (__uint_as_float(l1.z) + __uint_as_float(l1.w)));
        if (tid == 0) st_async_v2(mapa(sb + OFF_ML, rank ^ 1), __float_as_uint(mloc), __float_as_uint(lloc), mapa(bar_ml, rank ^ 1));
        mbar_wait(bar_ml, 0);
        const uint2 pml = lds64(sb + OFF_ML);
        const float mp = __uint_as_float(pml.x), lp = __uint_as_float(pml.y);
        const float M = fmaxf(mloc, mp);
        const float m_a = rank ? mp : mloc, l_a = rank ? lp : lloc, m_b = rank ? mloc : mp, l_b = rank ? lloc : lp;
        const float L = l_a * exp2f((m_a - M) * LOG2E) + l_b * exp2f((m_b - M) * LOG2E);
        const float inv = 1.0f / L;
        uint32_t pv[8];
#pragma unroll
        for (int i = 0; i < 8; i++)
            pv[i] = pack_bf(exp2f((bf_lo(sv[i]) - M) * LOG2E) * inv, exp2f((bf_hi(sv[i]) - M) * LOG2E) * inv);
        sts128(sb + OFF_SP + tid * 16, make_uint4(pv[0], pv[1], pv[2], pv[3]));
        sts128(sb + OFF_SP + 4096 + tid * 16, make_uint4(pv[4], pv[5], pv[6], pv[7]));
        cons_sync();
    }
    unsigned long long* acc1_dst = g_acc1 + b * D_MODEL + rank * 256 + warp * 32 + c * 8 + g;
    uint32_t o_dst = sb + OFF_O + (rank * 2 + (c & 1)) * O_STRIDE + (warp * 8 + g) * 4, o_bar = bar_o;
    if (c & 2) { o_dst = mapa(o_dst, rank ^ 1); o_bar = mapa(bar_o, rank ^ 1); }
    uint32_t o_src = sb + OFF_O + (rr & 3) * O_STRIDE + mi * 16;
    unsigned* tick_dst = g_tick + (bh & 7) * 32;
    asm volatile("" : "+l"(acc1_dst), "+l"(tick_dst), "+r"(o_dst), "+r"(o_bar), "+r"(o_src));
    const bool is_fin = bh < NFIN;
    const unsigned long long* p1 = g_acc1 + mb_ * D_MODEL + warp * 64 + j4 * 8 + c * 2;
    uint4* part_dst = g_part + ((warp * 4 + c) * NMLP + bh) * 8 + g;
    const uint4* inbox = g_part + bh * (NMLP * 8) + tid;
    const uint4* inbox2 = tid < (NMLP - 32) * 8 ? inbox + 256 : inbox;
    const uint4* inbox_pf = g_part + (bh * NMLP + tid) * 8;
    int do_pf = is_fin && tid < NMLP;
    float wsel = tid < (NMLP - 32) * 8 ? 1.0f : 0.0f;
    __nv_bfloat16* out_dst = out + ((lane >> 3) & 1) * D_MODEL + bh * 16 + (lane >> 4) * 8 + (lane & 7);
    asm volatile("" : "+l"(p1), "+l"(part_dst), "+l"(inbox), "+l"(inbox2), "+l"(inbox_pf), "+r"(do_pf), "+f"(wsel), "+l"(out_dst));
    uint32_t xv[2] = {lds32(sb + OFF_X + (mb_ * D_MODEL + d0) * 2), lds32(sb + OFF_X + (mb_ * D_MODEL + d0 + 8) * 2)};
    float b1v = bf16_at(sb + OFF_X + 3072 + lane * 2);
    float b2v = bf16_at(sb + OFF_X + 2048 + ((bh & 31) * 16 + (lane >> 4) * 8 + (lane & 7)) * 2);
    uint32_t a_part = sb + OFF_PART + warp * 256 + ((c >> 1) * 32 + (c & 1) * 16 + g) * 4;
    uint32_t a_stat = sb + OFF_STAT + (mb_ * 16 + (c & 1) * 8 + warp) * 4;
    uint32_t a_keep = sb + OFF_RED + mb_ * 32 + c * 4;
    uint32_t a_sum = sb + OFF_PART + (warp * 32 + lane) * 4, a_cs = sb + OFF_CS + lane * 4;
    uint32_t a_hid = sb + OFF_HID + warp * 80 + lane * 2, a_hidb = sb + OFF_HID + (rr & 1) * 80 + mi * 16;
    uint32_t a_fin = sb + OFF_PART + warp * 256 + lane * 4;
    uint32_t a_hfin = sb + OFF_RED + ((lane >> 3) & 1) * 32 + ((lane >> 4) * 8 + (lane & 7)) * 2;
    int keep_h = warp * 4 + j4 == bh;
    asm volatile("" : "+r"(a_part), "+r"(a_stat), "+r"(a_keep), "+r"(a_sum), "+r"(a_cs), "+r"(a_hid), "+r"(a_hidb), "+r"(a_fin), "+r"(a_hfin),
                 "+r"(keep_h), "+f"(b1v), "+f"(b2v));
    static_assert(T_W1 % NST + 3 < NST, "w1/w2 occupy four consecutive slots with the same parity");
    constexpr int W_PAR = (T_W1 / NST) & 1;
    uint32_t w1_bar = bar_full + (T_W1 % NST + (warp >> 2)) * 8;
    uint32_t w1_a = sb + OFF_RING + (T_W1 % NST + (warp >> 2)) * TILE_BYTES + ((warp & 3) * 64 + (mi >> 1) * 8 + rr) * 64 + ((mi & 1) ^ (rr >> 1)) * 16;
    uint32_t w2_a = sb + OFF_RING + (T_W2 % NST + (warp >> 2)) * TILE_BYTES + (warp & 3) * 4096 + ((mi >> 1) * 8 + rr) * 128 + ((mi & 1) ^ rr) * 16;
    asm volatile("" : "+r"(w1_bar), "+r"(w1_a), "+r"(w2_a));
    {
        const int hh = warp >> 2, ch = 2 * (warp & 3);
        const int line = 2 * (8 * (mi >> 1) + rr) + hh;
        uint32_t voff = sb + OFF_RING + line * 128 + (((ch ^ (mi & 1) ^ (rr >> 2)) ^ (line & 7)) * 16);
        uint32_t pmask = ((c >> 1) == (g & 1)) ? 0xffffffffu : 0u;
        asm volatile("" : "+r"(voff), "+r"(pmask));
        uint32_t paddr = sb + OFF_SP + c * 32;
        float o0[4] = {0.f, 0.f, 0.f, 0.f}, o1[4] = {0.f, 0.f, 0.f, 0.f};
#pragma unroll 1
        for (int i = 0; i < NTILE; i++) {
            const uint32_t base = voff + st * TILE_BYTES;
            uint4 p0 = lds128(paddr), p1 = lds128(paddr + 16);
            p0.x &= pmask; p0.y &= pmask; p0.z &= pmask; p0.w &= pmask;
            p1.x &= pmask; p1.y &= pmask; p1.z &= pmask; p1.w &= pmask;
            asm volatile("" : "+r"(p0.x), "+r"(p0.y), "+r"(p0.z), "+r"(p0.w), "+r"(p1.x), "+r"(p1.y), "+r"(p1.z), "+r"(p1.w));
            mbar_wait(bar_full + st * 8, ph);
            uint32_t a0[4], a1[4], a2[4], a3[4];
            ldsm4t(a0, base); ldsm4t(a1, base + 4096); ldsm4t(a2, base + 8192); ldsm4t(a3, base + 12288);
            if (i == NTILE - 1 && tid == 0) {
                asm volatile("red.relaxed.gpu.global.add.u32 [%0], 1;" ::"l"(tick_dst) : "memory");
                mbar_arrive(bar_end);
            }
            mma_bf16(o0, a0[0], a0[1], a0[2], a0[3], p0.x, p0.y);
            mma_bf16(o1, a1[0], a1[1], a1[2], a1[3], p0.z, p0.w);
            mma_bf16(o0, a2[0], a2[1], a2[2], a2[3], p1.x, p1.y);
            mma_bf16(o1, a3[0], a3[1], a3[2], a3[3], p1.z, p1.w);
            __syncwarp();
            if (lane == 0) mbar_arrive(bar_empty + st * 8);
            paddr += TILE_KEYS * 2;
            if (++st == NST) { st = 0; ph ^= 1; }
        }
        const float v0 = (o0[0] + o1[0]) + (o0[3] + o1[3]);
        const float v1 = (o0[1] + o1[1]) + (o0[2] + o1[2]);
        const uint32_t hi = pack_bf(v0, v1);
        const uint32_t val = (c & 1) ? pack_bf(v0 - bf_lo(hi), v1 - bf_hi(hi)) : hi;
        if (c & 2) st_async_b32(o_dst, val, o_bar);
        else sts32(o_dst, val);
        __syncwarp();
        if (lane == 0) mbar_arrive(bar_o);
        mbar_wait(bar_o, 0);
    }
    {
        float d00[4] = {0.f, 0.f, 0.f, 0.f}, d01[4] = {0.f, 0.f, 0.f, 0.f}, d10[4] = {0.f, 0.f, 0.f, 0.f}, d11[4] = {0.f, 0.f, 0.f, 0.f};
        uint32_t ob[4][4];
#pragma unroll
        for (int t = 0; t < 4; t++) ldsm4(ob[t], o_src + t * 64);
#pragma unroll
        for (int t = 0; t < 4; t++) {
            mma_bf16(d00, wf[16 * t], wf[16 * t + 1], wf[16 * t + 2], wf[16 * t + 3], ob[t][0], ob[t][1]);
            mma_bf16(d10, wf[16 * t + 4], wf[16 * t + 5], wf[16 * t + 6], wf[16 * t + 7], ob[t][0], ob[t][1]);
            mma_bf16(d01, wf[16 * t + 8], wf[16 * t + 9], wf[16 * t + 10], wf[16 * t + 11], ob[t][2], ob[t][3]);
            mma_bf16(d11, wf[16 * t + 12], wf[16 * t + 13], wf[16 * t + 14], wf[16 * t + 15], ob[t][2], ob[t][3]);
        }
        const float e0 = (d00[0] + d01[0]) + (d00[1] + d01[1]), e1 = (d00[2] + d01[2]) + (d00[3] + d01[3]);
        const float e2 = (d10[0] + d11[0]) + (d10[1] + d11[1]), e3 = (d10[2] + d11[2]) + (d10[3] + d11[3]);
        const float ea = (c & 2) ? e2 : e0, eb = (c & 2) ? e3 : e1;
        const float e = ((c & 1) ? eb : ea) + __shfl_xor_sync(~0u, (c & 1) ? ea : eb, 1);
        red_add64(acc1_dst, fx_encode(e));
    }
    if (!is_mlp) return;

    {
        if (do_pf) asm volatile("prefetch.global.L2 [%0];" ::"l"(inbox_pf));
        uint32_t* a1 = wf;
        uint32_t* a2 = wf + 32;
        auto load_w1 = [&]() {
#pragma unroll
            for (int k = 0; k < 4; k++) {
                ldsm4t(*(uint32_t(*)[4])(a1 + 8 * k), w1_a + k * 1024);
                ldsm4t(*(uint32_t(*)[4])(a1 + 8 * k + 4), (w1_a ^ 32) + k * 1024);
            }
        };
        auto load_w2 = [&]() {
#pragma unroll
            for (int u = 0; u < 2; u++)
#pragma unroll
                for (int T = 0; T < 4; T++) ldsm4t(*(uint32_t(*)[4])(a2 + 16 * u + 4 * T), (w2_a ^ (T * 32)) + u * 2048);
        };
        uint32_t hb0, hb1;
        int stage = 0;
        {
            uint4 ua = make_uint4(0, 0, 0, 0), ub = ua;
            int n = 0, polled = 0;
#pragma unroll 1
            do {
                if (!polled && __all_sync(~0u, mbar_test(bar_go, 0))) {
                    ld_relaxed2x64(ua, p1); ld_relaxed2x64(ub, p1 + 32);
                    polled = 1;
                }
                if (stage < 2 && __all_sync(~0u, mbar_test(w1_bar + stage * 16, W_PAR))) {
                    if (stage == 0) load_w1(); else load_w2();
                    stage++;
                }
                if (++n > SPIN_LIMIT * 16) __trap();
            } while (stage < 1 || !polled);
            if (stage < 2 && __all_sync(~0u, mbar_test(w1_bar + 16, W_PAR))) { load_w2(); stage = 2; }
            n = 0;
            while (!all_complete(ua, ub)) {
                ld_relaxed2x64(ua, p1); ld_relaxed2x64(ub, p1 + 32);
                if (++n > SPIN_LIMIT) __trap();
            }
            const uint32_t at0 = pack_bf(fx_decode(ua.x, ua.y), fx_decode(ua.z, ua.w)), at1 = pack_bf(fx_decode(ub.x, ub.y), fx_decode(ub.z, ub.w));
            hb0 = pack_bf(bf_lo(xv[0]) + bf_lo(at0), bf_hi(xv[0]) + bf_hi(at0));
            hb1 = pack_bf(bf_lo(xv[1]) + bf_lo(at1), bf_hi(xv[1]) + bf_hi(at1));
        }
        gemv1_partial(a1, hb0, hb1, j4, c, a_part);
        {
            const float h0 = bf_lo(hb0), h1 = bf_hi(hb0), h2 = bf_lo(hb1), h3 = bf_hi(hb1);
            const float s1 = (h0 + h1) + (h2 + h3);
            const float s2 = (h0 * h0 + h1 * h1) + (h2 * h2 + h3 * h3);
            float t = ((c & 1) ? s2 : s1) + __shfl_xor_sync(~0u, (c & 1) ? s1 : s2, 1);
            t += __shfl_xor_sync(~0u, t, 2);
            t += __shfl_xor_sync(~0u, t, 8);
            t += __shfl_xor_sync(~0u, t, 16);
            if ((lane & 0x1a) == 0) sts32(a_stat, __float_as_uint(t));
        }
        if (keep_h) {
            sts32(a_keep, hb0);
            sts32(a_keep + 16, hb1);
        }
        asm volatile("bar.sync 2, 288;" ::: "memory");
        if (warp < 2) {
            const uint4 q0 = lds128(sb + OFF_STAT + warp * 64), q1 = lds128(sb + OFF_STAT + warp * 64 + 16);
            const uint4 q2 = lds128(sb + OFF_STAT + warp * 64 + 32), q3 = lds128(sb + OFF_STAT + warp * 64 + 48);
            const float sacc = sum8(a_sum);
            const float cs = __uint_as_float(lds32(a_cs));
            const float mean = (((__uint_as_float(q0.x) + __uint_as_float(q0.y)) + (__uint_as_float(q0.z) + __uint_as_float(q0.w))) +
                                ((__uint_as_float(q1.x) + __uint_as_float(q1.y)) + (__uint_as_float(q1.z) + __uint_as_float(q1.w)))) * (1.0f / D_MODEL);
            const float msq = (((__uint_as_float(q2.x) + __uint_as_float(q2.y)) + (__uint_as_float(q2.z) + __uint_as_float(q2.w))) +
                               ((__uint_as_float(q3.x) + __uint_as_float(q3.y)) + (__uint_as_float(q3.z) + __uint_as_float(q3.w)))) * (1.0f / D_MODEL);
            const float var = fmaxf(msq - mean * mean, 0.f);
            float sq, iden;
            asm("sqrt.approx.ftz.f32 %0, %1;" : "=f"(sq) : "f"(rnd_bf(rnd_bf(var) + 1e-5f)));
            asm("rcp.approx.ftz.f32 %0, %1;" : "=f"(iden) : "f"(rnd_bf(sq)));
            const float z = fmaxf(rnd_bf(rnd_bf((sacc - rnd_bf(mean) * cs) * iden) + b1v), 0.f);
            sts16(a_hid, (uint16_t)pack_bf(z * z, 0.f));
        }
        if (stage < 2) { mbar_wait(w1_bar + 16, W_PAR); load_w2(); }
        cons_sync();
        uint32_t hb[4];
        ldsm4(hb, a_hidb);
        const float hfin = bf16_at(a_hfin);
        float y[4][4];
#pragma unroll
        for (int T = 0; T < 4; T++) {
            y[T][0] = y[T][1] = y[T][2] = y[T][3] = 0.f;
            mma_bf16(y[T], a2[4 * T], a2[4 * T + 1], a2[4 * T + 2], a2[4 * T + 3], hb[0], hb[1]);
        }
#pragma unroll
        for (int T = 0; T < 4; T++)
            mma_bf16(y[T], a2[16 + 4 * T], a2[16 + 4 * T + 1], a2[16 + 4 * T + 2], a2[16 + 4 * T + 3], hb[2], hb[3]);
        {
            const bool up2 = c & 2, up1 = c & 1;
            uint32_t e[4];
#pragma unroll
            for (int i = 0; i < 4; i++) e[i] = __float_as_uint(up2 ? (up1 ? y[3][i] : y[2][i]) : (up1 ? y[1][i] : y[0][i])) | 1u;
            asm volatile("st.relaxed.gpu.global.v4.u32 [%0], {%1,%2,%3,%4};" ::"l"(part_dst), "r"(e[0]), "r"(e[1]), "r"(e[2]), "r"(e[3]) : "memory");
        }
        if (!is_fin) return;
        {
            uint4 u, w;
            int n = 0;
            spin_cycles(DELAY2);
            do {
                ld_relaxed128(u, inbox); ld_relaxed128(w, inbox2);
                if (++n > SPIN_LIMIT) __trap();
            } while (!all_marked(u, w));
            const float v0 = fmaf(__uint_as_float(w.x), wsel, __uint_as_float(u.x)), v1 = fmaf(__uint_as_float(w.y), wsel, __uint_as_float(u.y));
            const float v2 = fmaf(__uint_as_float(w.z), wsel, __uint_as_float(u.z)), v3 = fmaf(__uint_as_float(w.w), wsel, __uint_as_float(u.w));
            const bool up16 = lane & 16, up8 = lane & 8;
            const float r0 = (up16 ? v2 : v0) + __shfl_xor_sync(~0u, up16 ? v0 : v2, 16);
            const float r1 = (up16 ? v3 : v1) + __shfl_xor_sync(~0u, up16 ? v1 : v3, 16);
            const float r = (up8 ? r1 : r0) + __shfl_xor_sync(~0u, up8 ? r0 : r1, 8);
            sts32(a_fin, __float_as_uint(r));
        }
        cons_sync();
        if (warp == 0) {
            const float y2 = sum8(a_sum);
            *out_dst = __ushort_as_bfloat16((unsigned short)pack_bf(hfin + rnd_bf(rnd_bf(y2) + b2v), 0.f));
        }
        if (bh == 0) {
            *(ulonglong2*)(g_acc1 + tid * 4) = make_ulonglong2(0, 0);
            *(ulonglong2*)(g_acc1 + tid * 4 + 2) = make_ulonglong2(0, 0);
            if (tid < 8) g_tick[tid * 32] = 0;
        }
    }
}

typedef CUresult (*EncodeFn)(CUtensorMap*, CUtensorMapDataType, cuuint32_t, void*, const cuuint64_t*, const cuuint64_t*,
                             const cuuint32_t*, const cuuint32_t*, CUtensorMapInterleave, CUtensorMapSwizzle,
                             CUtensorMapL2promotion, CUtensorMapFloatOOBfill);

void make_map(EncodeFn enc, CUtensorMap* tm, void* ptr, uint64_t cols, uint64_t rows, uint32_t box_cols, uint32_t box_rows,
              CUtensorMapSwizzle swz) {
    const cuuint64_t dims[2] = {cols, rows};
    const cuuint64_t strides[1] = {cols * 2};
    const cuuint32_t box[2] = {box_cols, box_rows};
    const cuuint32_t es[2] = {1, 1};
    enc(tm, CU_TENSOR_MAP_DATA_TYPE_BFLOAT16, 2, ptr, dims, strides, box, es, CU_TENSOR_MAP_INTERLEAVE_NONE, swz,
        CU_TENSOR_MAP_L2_PROMOTION_NONE, CU_TENSOR_MAP_FLOAT_OOB_FILL_NONE);
}

}

extern "C" void kernel_launch(void* const* d_in, const int* in_sizes, int n_in, void* d_out, int out_size) {
    (void)in_sizes; (void)n_in; (void)out_size;
    static EncodeFn enc = nullptr;
    static Scratch* scr = nullptr;
    static uint32_t tile_ns_x16 = 0;
    if (!enc) {
        void* fn = nullptr;
        cudaDriverEntryPointQueryResult qr;
        cudaGetDriverEntryPoint("cuTensorMapEncodeTiled", &fn, cudaEnableDefault, &qr);
        enc = (EncodeFn)fn;
        cudaGetSymbolAddress((void**)&scr, g_scratch);
        int dev = 0, mem_khz = 0, bus_bits = 0;
        cudaGetDevice(&dev);
        cudaDeviceGetAttribute(&mem_khz, cudaDevAttrMemoryClockRate, dev);
        cudaDeviceGetAttribute(&bus_bits, cudaDevAttrGlobalMemoryBusWidth, dev);
        const double bytes_per_ns = 2.0 * mem_khz * 1e-6 * (bus_bits / 8) * (PACE * 1e-3);
        if (bytes_per_ns > 0) tile_ns_x16 = (uint32_t)(16.0 * NCTA * TILE_BYTES / bytes_per_ns);
        cudaFuncSetAttribute(decode_block_kernel, cudaFuncAttributeMaxDynamicSharedMemorySize, SMEM_BYTES);
    }
    Maps tm;
    make_map(enc, &tm.v, d_in[2], 64, (uint64_t)2 * NHEAD * SK * 2, 64, TILE_KEYS * 2, CU_TENSOR_MAP_SWIZZLE_128B);
    make_map(enc, &tm.wq, d_in[3], QCOLS, D_MODEL, 64, 128, CU_TENSOR_MAP_SWIZZLE_128B);
    make_map(enc, &tm.wo, d_in[4], D_MODEL, QCOLS, 64, 128, CU_TENSOR_MAP_SWIZZLE_128B);
    make_map(enc, &tm.w1, d_in[6], FF, D_MODEL, 32, 256, CU_TENSOR_MAP_SWIZZLE_64B);
    make_map(enc, &tm.w2, d_in[8], D_MODEL, FF, 64, 32, CU_TENSOR_MAP_SWIZZLE_128B);
    decode_block_kernel<<<NCTA, NTHREADS, SMEM_BYTES>>>(
        tm, (const __nv_bfloat16*)d_in[0], (const __nv_bfloat16*)d_in[1], (const __nv_bfloat16*)d_in[7],
        (const __nv_bfloat16*)d_in[9], (__nv_bfloat16*)d_out, scr, tile_ns_x16);
}
```

```cpp
#include <cuda_runtime.h>
#include <cuda_bf16.h>
#include <cuda.h>
#include <stdint.h>

namespace {

constexpr int D_MODEL = 512;
constexpr int NHEAD = 32;
constexpr int SK = 8192;
constexpr int DH = 128;
constexpr int FF = 1376;
constexpr int QCOLS = NHEAD * DH;

constexpr int NCTA = 128;
constexpr int KEYS_PER_CTA = SK / 2;
constexpr int TILE_KEYS = 64;
constexpr int TILE_BYTES = TILE_KEYS * DH * 2;
constexpr int NTILE = KEYS_PER_CTA / TILE_KEYS;
constexpr int NST = 12;
constexpr int NINIT = 5;
constexpr int WLATE = 1;
constexpr int LEAD = 7;
constexpr int PACE = 960;
constexpr int SKEW = 10;
constexpr int DELAY2 = 300;
constexpr int NCONS = 256;
constexpr int NTHREADS = NCONS + 64;
constexpr int NMLP = FF / 32;
constexpr int KPRE = NST - 4;
constexpr int T_WQ = 0, T_K0 = 4, T_WO = T_K0 + KPRE, T_K1 = T_WO + 4, T_V = T_K1 + NTILE - KPRE, T_W1 = T_V + NTILE,
              T_W2 = T_W1 + 2, T_END = T_W2 + 2;

constexpr int OFF_RING = 0;
constexpr int OFF_SP = OFF_RING + NST * TILE_BYTES;
constexpr int OFF_PART = OFF_SP + KEYS_PER_CTA * 2;
constexpr int OFF_CS = OFF_PART + 8 * 64 * 4;
constexpr int OFF_XN = OFF_CS + 32 * 4;
constexpr int OFF_X = OFF_XN + 1024;
constexpr int O_STRIDE = 272;
constexpr int OFF_O = OFF_X + 2048 + 1024 + 64;
constexpr int OFF_Q = OFF_O + 4 * O_STRIDE;
constexpr int OFF_RED = OFF_Q + 256;
constexpr int OFF_STAT = OFF_RED + 64;
constexpr int OFF_HID = OFF_STAT + 128;
constexpr int OFF_ML = OFF_HID + 160;
constexpr int OFF_BAR = OFF_ML + 16;
constexpr int SMEM_USED = OFF_BAR + (2 * NST + 5) * 8;
constexpr int SMEM_BYTES = SMEM_USED + 1024;

constexpr float FX_SCALE = 1073741824.0f;
constexpr float FX_INV = 1.0f / 1073741824.0f;

constexpr int NFIN = 32;
struct Scratch {
    unsigned long long acc1[2 * D_MODEL];
    unsigned int tick[8 * 32];
    uint4 part[NFIN * NMLP * 8];
};
__device__ __align__(1024) Scratch g_scratch;

__device__ __forceinline__ void mbar_init(uint32_t bar, uint32_t cnt) {
    asm volatile("mbarrier.init.shared::cta.b64 [%0], %1;" ::"r"(bar), "r"(cnt) : "memory");
}
__device__ __forceinline__ void mbar_expect_tx(uint32_t bar, uint32_t bytes) {
    asm volatile("mbarrier.arrive.expect_tx.shared::cta.b64 _, [%0], %1;" ::"r"(bar), "r"(bytes) : "memory");
}
__device__ __forceinline__ void mbar_arrive(uint32_t bar) {
    asm volatile("mbarrier.arrive.shared::cta.b64 _, [%0];" ::"r"(bar) : "memory");
}
__device__ __forceinline__ bool mbar_test(uint32_t bar, uint32_t parity) {
    uint32_t ok;
    asm volatile("{\n.reg .pred p;\nmbarrier.test_wait.parity.shared::cta.b64 p, [%1], %2;\nselp.u32 %0, 1, 0, p;\n}"
                 : "=r"(ok) : "r"(bar), "r"(parity) : "memory");
    return ok;
}
__device__ __forceinline__ bool mbar_try(uint32_t bar, uint32_t parity) {
    uint32_t ok;
    asm volatile("{\n.reg .pred p;\nmbarrier.try_wait.parity.shared::cta.b64 p, [%1], %2;\nselp.u32 %0, 1, 0, p;\n}"
                 : "=r"(ok) : "r"(bar), "r"(parity) : "memory");
    return ok;
}
constexpr int SPIN_LIMIT = 1 << 20;
__device__ __forceinline__ void mbar_wait(uint32_t bar, uint32_t parity) {
    int n = 0;
    while (!mbar_try(bar, parity)) { if (++n > SPIN_LIMIT) __trap(); }
}
__device__ __forceinline__ void bulk_load(uint32_t dst, const void* src, uint32_t bytes, uint32_t bar) {
    asm volatile("cp.async.bulk.shared::cluster.global.mbarrier::complete_tx::bytes [%0], [%1], %2, [%3];"
                 ::"r"(dst), "l"(src), "r"(bytes), "r"(bar) : "memory");
}
__device__ __forceinline__ void tma2d(uint32_t dst, const CUtensorMap* tm, int c0, int c1, uint32_t bar) {
    asm volatile("cp.async.bulk.tensor.2d.shared::cluster.global.mbarrier::complete_tx::bytes [%0], [%1, {%3, %4}], [%2];"
                 ::"r"(dst), "l"(tm), "r"(bar), "r"(c0), "r"(c1) : "memory");
}
__device__ __forceinline__ void bulk_load_stream(uint32_t dst, const void* src, uint32_t bytes, uint32_t bar, uint64_t pol) {
    asm volatile("cp.async.bulk.shared::cluster.global.mbarrier::complete_tx::bytes.L2::cache_hint [%0], [%1], %2, [%3], %4;"
                 ::"r"(dst), "l"(src), "r"(bytes), "r"(bar), "l"(pol) : "memory");
}
__device__ __forceinline__ void tma2d_stream(uint32_t dst, const CUtensorMap* tm, int c0, int c1, uint32_t bar, uint64_t pol) {
    asm volatile("cp.async.bulk.tensor.2d.shared::cluster.global.mbarrier::complete_tx::bytes.L2::cache_hint [%0], [%1, {%3, %4}], [%2], %5;"
                 ::"r"(dst), "l"(tm), "r"(bar), "r"(c0), "r"(c1), "l"(pol) : "memory");
}
__device__ __forceinline__ bool elect_one() {
    uint32_t p;
    asm volatile("{\n.reg .pred p;\nelect.sync _|p, 0xffffffff;\nselp.u32 %0, 1, 0, p;\n}" : "=r"(p));
    return p;
}
__device__ __forceinline__ void cons_sync() { asm volatile("bar.sync 1, 256;" ::: "memory"); }

__device__ __forceinline__ uint32_t mapa(uint32_t addr, uint32_t rank) {
    uint32_t r;
    asm("mapa.shared::cluster.u32 %0, %1, %2;" : "=r"(r) : "r"(addr), "r"(rank));
    return r;
}
__device__ __forceinline__ void st_async_b32(uint32_t addr, uint32_t v, uint32_t bar) {
    asm volatile("st.async.weak.shared::cluster.mbarrier::complete_tx::bytes.b32 [%0], %1, [%2];" ::"r"(addr), "r"(v), "r"(bar) : "memory");
}
__device__ __forceinline__ void st_async_v2(uint32_t addr, uint32_t v0, uint32_t v1, uint32_t bar) {
    asm volatile("st.async.weak.shared::cluster.mbarrier::complete_tx::bytes.v2.b32 [%0], {%1, %2}, [%3];" ::"r"(addr), "r"(v0), "r"(v1), "r"(bar) : "memory");
}

__device__ __forceinline__ void mma_bf16(float (&d)[4], uint32_t a0, uint32_t a1, uint32_t a2, uint32_t a3, uint32_t b0, uint32_t b1) {
    asm volatile("mma.sync.aligned.m16n8k16.row.col.f32.bf16.bf16.f32 {%0,%1,%2,%3}, {%4,%5,%6,%7}, {%8,%9}, {%0,%1,%2,%3};"
                 : "+f"(d[0]), "+f"(d[1]), "+f"(d[2]), "+f"(d[3])
                 : "r"(a0), "r"(a1), "r"(a2), "r"(a3), "r"(b0), "r"(b1));
}
__device__ __forceinline__ void ldsm4(uint32_t (&r)[4], uint32_t addr) {
    asm volatile("ldmatrix.sync.aligned.m8n8.x4.shared.b16 {%0,%1,%2,%3}, [%4];"
                 : "=r"(r[0]), "=r"(r[1]), "=r"(r[2]), "=r"(r[3]) : "r"(addr) : "memory");
}
__device__ __forceinline__ void ldsm4t(uint32_t (&r)[4], uint32_t addr) {
    asm volatile("ldmatrix.sync.aligned.m8n8.x4.trans.shared.b16 {%0,%1,%2,%3}, [%4];"
                 : "=r"(r[0]), "=r"(r[1]), "=r"(r[2]), "=r"(r[3]) : "r"(addr) : "memory");
}
__device__ __forceinline__ uint4 lds128(uint32_t a) {
    uint4 v;
    asm volatile("ld.shared.v4.u32 {%0,%1,%2,%3}, [%4];" : "=r"(v.x), "=r"(v.y), "=r"(v.z), "=r"(v.w) : "r"(a) : "memory");
    return v;
}
__device__ __forceinline__ uint2 lds64(uint32_t a) {
    uint2 v;
    asm volatile("ld.shared.v2.u32 {%0,%1}, [%2];" : "=r"(v.x), "=r"(v.y) : "r"(a) : "memory");
    return v;
}
__device__ __forceinline__ uint32_t lds32(uint32_t a) {
    uint32_t v;
    asm volatile("ld.shared.u32 %0, [%1];" : "=r"(v) : "r"(a) : "memory");
    return v;
}
__device__ __forceinline__ void sts128(uint32_t a, uint4 v) {
    asm volatile("st.shared.v4.u32 [%0], {%1,%2,%3,%4};" ::"r"(a), "r"(v.x), "r"(v.y), "r"(v.z), "r"(v.w) : "memory");
}
__device__ __forceinline__ void sts64(uint32_t a, uint32_t v0, uint32_t v1) {
    asm volatile("st.shared.v2.u32 [%0], {%1,%2};" ::"r"(a), "r"(v0), "r"(v1) : "memory");
}
__device__ __forceinline__ void sts32(uint32_t a, uint32_t v) {
    asm volatile("st.shared.u32 [%0], %1;" ::"r"(a), "r"(v) : "memory");
}
__device__ __forceinline__ void sts16(uint32_t a, uint16_t v) {
    asm volatile("st.shared.u16 [%0], %1;" ::"r"(a), "h"(v) : "memory");
}
__device__ __forceinline__ float bf_lo(uint32_t v) { return __uint_as_float(v << 16); }
__device__ __forceinline__ float bf_hi(uint32_t v) { return __uint_as_float(v & 0xffff0000u); }
__device__ __forceinline__ uint32_t pack_bf(float lo, float hi) {
    uint32_t r;
    asm("cvt.rn.bf16x2.f32 %0, %1, %2;" : "=r"(r) : "f"(hi), "f"(lo));
    return r;
}
__device__ __forceinline__ float rnd_bf(float v) { return bf_lo(pack_bf(v, 0.f)); }

__device__ __forceinline__ unsigned long long fx_encode(float v) {
    return ((unsigned long long)__float2ll_rn(v * FX_SCALE) << 8) + 1ull;
}
__device__ __forceinline__ float fx_decode(uint32_t lo, uint32_t hi) {
    return fmaf(__int2float_rn((int)hi), 1.0f / 64.0f, __uint2float_rn(lo & 0xffffff00u) * (FX_INV / 256.0f));
}
__device__ __forceinline__ uint32_t gtime32() {
    uint32_t t;
    asm volatile("mov.u32 %0, %%globaltimer_lo;" : "=r"(t));
    return t;
}
__device__ __forceinline__ void wait_until(uint32_t t0, uint32_t ns) {
    for (int n = 0; gtime32() - t0 < ns && n < SPIN_LIMIT; n++) {}
}
__device__ __forceinline__ void spin_cycles(uint32_t n) {
    uint32_t t0, t;
    asm volatile("mov.u32 %0, %%clock;" : "=r"(t0));
    do { asm volatile("mov.u32 %0, %%clock;" : "=r"(t)); } while (t - t0 < n);
}
__device__ __forceinline__ void red_add64(unsigned long long* p, unsigned long long v) {
    asm volatile("red.relaxed.gpu.global.add.u64 [%0], %1;" ::"l"(p), "l"(v) : "memory");
}
__device__ __forceinline__ void ld_relaxed2x64(uint4& v, const void* p) {
    asm volatile("{\n.reg .b64 a, b;\nld.relaxed.gpu.global.v2.b64 {a, b}, [%4];\nmov.b64 {%0, %1}, a;\nmov.b64 {%2, %3}, b;\n}"
                 : "=r"(v.x), "=r"(v.y), "=r"(v.z), "=r"(v.w) : "l"(p) : "memory");
}
__device__ __forceinline__ void ld_relaxed128(uint4& v, const uint4* p) {
    asm volatile("ld.relaxed.gpu.global.v4.u32 {%0,%1,%2,%3}, [%4];" : "=r"(v.x), "=r"(v.y), "=r"(v.z), "=r"(v.w) : "l"(p) : "memory");
}
__device__ __forceinline__ uint32_t and3(uint32_t a, uint32_t b, uint32_t c) {
    uint32_t r;
    asm("lop3.b32 %0, %1, %2, %3, 0x80;" : "=r"(r) : "r"(a), "r"(b), "r"(c));
    return r;
}
__device__ __forceinline__ bool all_marked(const uint4& a, const uint4& b) {
    return __all_sync(~0u, and3(and3(a.x, a.y, a.z), and3(a.w, b.x, b.y), and3(b.z, b.w, 1u)));
}
__device__ __forceinline__ bool all_complete(const uint4& a, const uint4& b) {
    return __all_sync(~0u, and3(and3(a.x, a.z, b.x), b.z, 32u));
}
__device__ __forceinline__ float bf16_at(uint32_t a) {
    uint16_t v;
    asm volatile("ld.shared.u16 %0, [%1];" : "=h"(v) : "r"(a) : "memory");
    return __uint_as_float((uint32_t)v << 16);
}

__device__ __forceinline__ int bpos(int k) { return ((k >> 1) & 3) * 16 + ((k >> 4) & 3) * 4 + ((k >> 3) & 1) * 2 + (k & 1); }

__device__ __forceinline__ void gemv1_partial(const uint32_t* a1, uint32_t hb0, uint32_t hb1, int j, int c, uint32_t a) {
    float t0[4] = {0.f, 0.f, 0.f, 0.f}, t1[4] = {0.f, 0.f, 0.f, 0.f}, t2[4] = {0.f, 0.f, 0.f, 0.f}, t3[4] = {0.f, 0.f, 0.f, 0.f};
#pragma unroll
    for (int k = 0; k < 2; k++) {
        const uint32_t m0 = (j == k) ? hb0 : 0u, m1 = (j == k) ? hb1 : 0u;
        const uint32_t n0 = (j == k + 2) ? hb0 : 0u, n1 = (j == k + 2) ? hb1 : 0u;
        mma_bf16(t0, a1[8 * k], a1[8 * k + 1], a1[8 * k + 2], a1[8 * k + 3], m0, m1);
        mma_bf16(t1, a1[8 * k + 4], a1[8 * k + 5], a1[8 * k + 6], a1[8 * k + 7], m0, m1);
        mma_bf16(t2, a1[8 * k + 16], a1[8 * k + 17], a1[8 * k + 18], a1[8 * k + 19], n0, n1);
        mma_bf16(t3, a1[8 * k + 20], a1[8 * k + 21], a1[8 * k + 22], a1[8 * k + 23], n0, n1);
    }
    const bool up2 = c & 2, up1 = c & 1;
    float r4[4], r2[2];
    const float send[4] = {up2 ? t2[0] : t0[1], up2 ? t2[2] : t0[3], up2 ? t3[0] : t1[1], up2 ? t3[2] : t1[3]};
    const float keep[4] = {up2 ? t2[1] : t0[0], up2 ? t2[3] : t0[2], up2 ? t3[1] : t1[0], up2 ? t3[3] : t1[2]};
#pragma unroll
    for (int i = 0; i < 4; i++) r4[i] = keep[i] + __shfl_xor_sync(~0u, send[i], 2);
#pragma unroll
    for (int i = 0; i < 2; i++) r2[i] = (up1 ? r4[i + 2] : r4[i]) + __shfl_xor_sync(~0u, up1 ? r4[i] : r4[i + 2], 1);
    sts32(a, __float_as_uint(r2[0]));
    sts32(a + 32, __float_as_uint(r2[1]));
}

__device__ __forceinline__ float sum8(uint32_t a) {
    float p[8];
#pragma unroll
    for (int w = 0; w < 8; w++) p[w] = __uint_as_float(lds32(a + w * 256));
    return ((p[0] + p[1]) + (p[2] + p[3])) + ((p[4] + p[5]) + (p[6] + p[7]));
}

struct Maps { CUtensorMap v, wq, wo, w1, w2; };

__global__ void __cluster_dims__(2, 1, 1) __launch_bounds__(NTHREADS, 1)
decode_block_kernel(const __grid_constant__ Maps tm,
                    const __nv_bfloat16* __restrict__ x, const __nv_bfloat16* __restrict__ Kc,
                    const __nv_bfloat16* __restrict__ b1, const __nv_bfloat16* __restrict__ b2,
                    __nv_bfloat16* __restrict__ out, Scratch* __restrict__ scr, uint32_t tile_ns_x16) {
    unsigned long long* const g_acc1 = scr->acc1;
    unsigned int* const g_tick = scr->tick;
    uint4* const g_part = scr->part;
    extern __shared__ unsigned char smem_raw[];
    const uint32_t sb = ((uint32_t)__cvta_generic_to_shared(smem_raw) + 1023u) & ~1023u;
    const uint32_t bar_full = sb + OFF_BAR, bar_empty = bar_full + NST * 8;
    const uint32_t bar_q = bar_empty + NST * 8, bar_ml = bar_q + 8, bar_o = bar_ml + 8, bar_end = bar_o + 8, bar_go = bar_end + 8;

    const char* ksrc = (const char*)Kc + (size_t)blockIdx.x * (KEYS_PER_CTA * DH * 2);
    constexpr uint64_t pol = 0x12F0000000000000ull;
    if (threadIdx.x == 0) {
        mbar_init(bar_full + T_K0 * 8, 1);
        asm volatile("fence.mbarrier_init.release.cluster;" ::: "memory");
        mbar_expect_tx(bar_full + T_K0 * 8, TILE_BYTES);
        bulk_load_stream(sb + OFF_RING + T_K0 * TILE_BYTES, ksrc, TILE_BYTES, bar_full + T_K0 * 8, pol);
    }
    int tid = threadIdx.x;
    asm volatile("" : "+r"(tid));
    const int lane = tid & 31;
    const int warp = __shfl_sync(~0u, tid >> 5, 0);
    const int bh = blockIdx.x >> 1, rank = blockIdx.x & 1;
    const int b = bh >> 5, h = bh & 31;
    const bool is_mlp = (rank == 0) && (bh < NMLP);
    const int f0 = bh * 32;

    if (elect_one()) {
        if (warp < 6) {
            if (warp >= 1) {
                const int s = warp < 2 ? T_K0 + warp : warp - 2;
                const uint32_t fb = bar_full + s * 8;
                mbar_init(fb, 1);
                asm volatile("fence.mbarrier_init.release.cluster;" ::: "memory");
                mbar_expect_tx(fb, TILE_BYTES);
                if (warp < 2) bulk_load_stream(sb + OFF_RING + s * TILE_BYTES, ksrc + (size_t)warp * TILE_BYTES, TILE_BYTES, fb, pol);
                else tma2d(sb + OFF_RING + s * TILE_BYTES, &tm.wq, h * DH + rank * 64, s * 128, fb);
            }
        } else if (warp == 7) {
#pragma unroll
            for (int s = 0; s < NST; s++) mbar_init(bar_empty + s * 8, 8);
            asm volatile("fence.mbarrier_init.release.cluster;" ::: "memory");
        } else if (warp == 8) {
#pragma unroll
            for (int s = T_K0 + 2; s < NST; s++) mbar_init(bar_full + s * 8, 1);
            asm volatile("fence.mbarrier_init.release.cluster;" ::: "memory");
#pragma unroll
            for (int s = T_K0 + 2; s < T_K0 + NINIT; s++) {
                mbar_expect_tx(bar_full + s * 8, TILE_BYTES);
                bulk_load_stream(sb + OFF_RING + s * TILE_BYTES, ksrc + (size_t)(s - T_K0) * TILE_BYTES, TILE_BYTES, bar_full + s * 8, pol);
            }
        } else if (warp == 9) {
            mbar_init(bar_q, 2); mbar_init(bar_ml, 1); mbar_init(bar_o, 10); mbar_init(bar_end, 1); mbar_init(bar_go, 1);
            asm volatile("fence.mbarrier_init.release.cluster;" ::: "memory");
            mbar_expect_tx(bar_q, 128);
            mbar_expect_tx(bar_ml, is_mlp ? 8 + 2048 + 1024 + 64 : 8);
            if (is_mlp) {
                bulk_load(sb + OFF_X, x, 2048, bar_ml);
                bulk_load(sb + OFF_X + 2048, b2, 1024, bar_ml);
                bulk_load(sb + OFF_X + 3072, b1 + f0, 64, bar_ml);
            }
            mbar_expect_tx(bar_o, 512);
            asm volatile("prefetch.tensormap [%0];" ::"l"(&tm.wo) : "memory");
            asm volatile("prefetch.tensormap [%0];" ::"l"(&tm.v) : "memory");
            asm volatile("prefetch.tensormap [%0];" ::"l"(&tm.w1) : "memory");
            asm volatile("prefetch.tensormap [%0];" ::"l"(&tm.w2) : "memory");
        }
    }
    __syncwarp();
    asm volatile("barrier.cluster.arrive.relaxed.aligned;" ::: "memory");

    if (warp == 8) {
        const uint32_t t_start = gtime32();
        asm volatile("barrier.cluster.wait.aligned;" ::: "memory");
        if (lane == 0) {
#pragma unroll
            for (int w = 0; w < 4; w++) mbar_wait(bar_full + (T_WQ + w) * 8, 0);
#pragma unroll
            for (int k = NINIT; k < KPRE; k++) {
                const uint32_t fb = bar_full + (T_K0 + k) * 8;
                mbar_expect_tx(fb, TILE_BYTES);
                bulk_load_stream(sb + OFF_RING + (T_K0 + k) * TILE_BYTES, ksrc + (size_t)k * TILE_BYTES, TILE_BYTES, fb, pol);
            }
            const int vline0 = (bh * SK + rank * KEYS_PER_CTA) * 2;
            const int tend = is_mlp ? T_END : T_W1;
            const int lead16 = LEAD * 16 + (bh < NMLP ? SKEW : -2 * SKEW);
            int st = 0, ph = 0;
#pragma unroll 1
            for (int t = NST; t < tend; t++) {
                const uint32_t dst = sb + OFF_RING + st * TILE_BYTES, fb = bar_full + st * 8;
                mbar_wait(bar_empty + st * 8, ph);
                wait_until(t_start, ((t * 16 - lead16) * tile_ns_x16) >> 8);
                if (t == T_W1) {
                    mbar_wait(bar_full + ((T_W1 - 1 - WLATE) % NST) * 8, ((T_W1 - 1 - WLATE) / NST) & 1);
                }
                mbar_expect_tx(fb, TILE_BYTES);
                if (t < T_K1) {
                    tma2d(dst, &tm.wo, rank * 256 + (t - T_WO) * 64, h * DH, fb);
                } else if (t < T_V) {
                    bulk_load_stream(dst, ksrc + (size_t)(t - 8) * TILE_BYTES, TILE_BYTES, fb, pol);
                } else if (t < T_W1) {
                    tma2d_stream(dst, &tm.v, 0, vline0 + (t - T_V) * (TILE_KEYS * 2), fb, pol);
                } else if (t < T_W2) {
                    tma2d(dst, &tm.w1, f0, (t - T_W1) * 256, fb);
                } else {
#pragma unroll
                    for (int i = 0; i < 4; i++) tma2d(dst + i * 4096, &tm.w2, ((t - T_W2) * 4 + i) * 64, f0, fb);
                }
                if (++st == NST) { st = 0; ph ^= 1; }
            }
        }
        if (is_mlp) {
            __syncwarp();
            const int rr = lane & 7, mi = lane >> 3;
            float cs[4][4];
#pragma unroll
            for (int i = 0; i < 4; i++) cs[i][0] = cs[i][1] = cs[i][2] = cs[i][3] = 0.f;
#pragma unroll
            for (int t = 0; t < 2; t++) {
                const uint32_t a = sb + OFF_RING + (T_W1 % NST + t) * TILE_BYTES + ((mi >> 1) * 8 + rr) * 64 + ((mi & 1) ^ (rr >> 1)) * 16;
                mbar_wait(bar_full + (T_W1 % NST + t) * 8, (T_W1 / NST) & 1);
#pragma unroll 4
                for (int k = 0; k < 16; k += 2) {
                    uint32_t w[4][4];
                    ldsm4t(w[0], a + k * 1024); ldsm4t(w[1], (a ^ 32) + k * 1024);
                    ldsm4t(w[2], a + k * 1024 + 1024); ldsm4t(w[3], (a ^ 32) + k * 1024 + 1024);
#pragma unroll
                    for (int i = 0; i < 4; i++) mma_bf16(cs[i], w[i][0], w[i][1], w[i][2], w[i][3], 0x3f803f80u, 0x3f803f80u);
                }
            }
            const int c = lane & 3;
            const float lo = (c & 1) ? cs[0][2] + cs[2][2] : cs[0][0] + cs[2][0], hi = (c & 1) ? cs[1][2] + cs[3][2] : cs[1][0] + cs[3][0];
            sts32(sb + OFF_CS + (c * 8 + (lane >> 2)) * 4, __float_as_uint((c & 2) ? hi : lo));
            asm volatile("bar.arrive 2, 288;" ::: "memory");
        }
        return;
    }

    if (warp == 9) {
        if (is_mlp) {
#pragma unroll
            for (int i = 0; i < 8; i++) g_part[((i * 4 + (lane >> 3)) * NMLP + bh) * 8 + (lane & 7)] = make_uint4(0, 0, 0, 0);
            __threadfence();
        }
        asm volatile("barrier.cluster.wait.aligned;" ::: "memory");
        if (lane == 0) mbar_arrive(bar_o);
        if (is_mlp) {
            mbar_wait(bar_end, 0);
            for (int n = 0;; n++) {
                unsigned v = 0;
                if (lane < 8) asm volatile("ld.relaxed.gpu.global.u32 %0, [%1];" : "=r"(v) : "l"(g_tick + lane * 32) : "memory");
                if (__reduce_add_sync(~0u, v) >= NCTA) break;
                if (n > SPIN_LIMIT) __trap();
            }
            if (lane == 0) mbar_arrive(bar_go);
        }
        return;
    }

    const int g = lane >> 2, c = lane & 3;
    const int rr = lane & 7, mi = lane >> 3;
    const int mb_ = g & 1, j4 = g >> 1;
    const int d0 = warp * 64 + j4 * 16 + c * 2;
    uint32_t qa[16], wf[64];
    {
        if (warp == 6) {
            const uint4 xa0 = __ldg((const uint4*)(x + b * D_MODEL) + lane), xa1 = __ldg((const uint4*)(x + b * D_MODEL) + 32 + lane);
            const uint32_t xa[8] = {xa0.x, xa0.y, xa0.z, xa0.w, xa1.x, xa1.y, xa1.z, xa1.w};
            float s = 0.f;
#pragma unroll
            for (int i = 0; i < 8; i++) s += bf_lo(xa[i]) + bf_hi(xa[i]);
#pragma unroll
            for (int o = 16; o; o >>= 1) s += __shfl_xor_sync(~0u, s, o);
            const float mean = s * (1.0f / D_MODEL);
            float v = 0.f;
#pragma unroll
            for (int i = 0; i < 8; i++) { const float e0 = bf_lo(xa[i]) - mean, e1 = bf_hi(xa[i]) - mean; v += e0 * e0 + e1 * e1; }
#pragma unroll
            for (int o = 16; o; o >>= 1) v += __shfl_xor_sync(~0u, v, o);
            const float mb = rnd_bf(mean);
            const float den = rnd_bf(sqrtf(rnd_bf(rnd_bf(v * (1.0f / D_MODEL)) + 1e-5f)));
#pragma unroll
            for (int i = 0; i < 8; i++) {
                const int k = (i >> 2) * 256 + lane * 8 + (i & 3) * 2;
                sts32(sb + OFF_XN + ((k & ~63) + bpos(k)) * 2,
                      pack_bf(__fdiv_rn(rnd_bf(bf_lo(xa[i]) - mb), den), __fdiv_rn(rnd_bf(bf_hi(xa[i]) - mb), den)));
            }
        }
        asm volatile("barrier.cluster.wait.aligned;" ::: "memory");
        cons_sync();

        float q0[4] = {0.f, 0.f, 0.f, 0.f}, q1[4] = {0.f, 0.f, 0.f, 0.f};
        const uint32_t aoff = ((warp >> 2) * 64 + (mi >> 1) * 8 + rr) * 128 + (((warp & 3) * 2 + (mi & 1)) ^ rr) * 16;
#pragma unroll
        for (int t = 0; t < 4; t++) {
            const uint32_t xaddr = sb + OFF_XN + (t * 2 + (warp >> 2)) * 128 + c * 32;
            const uint4 p0 = lds128(xaddr), p1 = lds128(xaddr + 16);
            const uint32_t base = sb + OFF_RING + (T_WQ + t) * TILE_BYTES + aoff;
            mbar_wait(bar_full + (T_WQ + t) * 8, 0);
            uint32_t a0[4], a1[4], a2[4], a3[4];
            ldsm4t(a0, base); ldsm4t(a1, base + 2048); ldsm4t(a2, base + 4096); ldsm4t(a3, base + 6144);
            mma_bf16(q0, a0[0], a0[1], a0[2], a0[3], p0.x, p0.y);
            mma_bf16(q1, a1[0], a1[1], a1[2], a1[3], p0.z, p0.w);
            mma_bf16(q0, a2[0], a2[1], a2[2], a2[3], p1.x, p1.y);
            mma_bf16(q1, a3[0], a3[1], a3[2], a3[3], p1.z, p1.w);
            __syncwarp();
            if (lane == 0) mbar_arrive(bar_empty + (T_WQ + t) * 8);
        }
        if (c < 2) sts32(sb + OFF_PART + (warp * 16 + c * 8 + g) * 4, __float_as_uint(c ? q0[2] + q1[2] : q0[0] + q1[0]));
        cons_sync();
        if (warp == 0) {
            const uint2 u = lds64(sb + OFF_PART + lane * 8), w = lds64(sb + OFF_PART + 256 + lane * 8);
            const uint32_t qq = pack_bf(__uint_as_float(u.x) + __uint_as_float(w.x), __uint_as_float(u.y) + __uint_as_float(w.y));
            const uint32_t dst = sb + OFF_Q + rank * 128 + lane * 4;
            sts32(dst, qq);
            st_async_b32(mapa(dst, rank ^ 1), qq, mapa(bar_q, rank ^ 1));
            __syncwarp();
            if (lane == 0) mbar_arrive(bar_q);
        }
        mbar_wait(bar_q, 0);
#pragma unroll
        for (int j = 0; j < 16; j++) qa[j] = lds32(sb + OFF_Q + ((j & 8) + ((g + j) & 7)) * 16 + c * 4);
    }

    int st = T_K0, ph = 0;
    float mx = -INFINITY;
    {
        uint32_t koff0 = sb + OFF_RING + (warp * 8 + rr) * 256 + ((rr + mi) & 7) * 16;
        uint32_t koff1 = sb + OFF_RING + (warp * 8 + rr) * 256 + ((rr + mi + 4) & 7) * 16;
        asm volatile("" : "+r"(koff0), "+r"(koff1));
        const bool valid = (c == (g >> 1));
        uint32_t spos = sb + OFF_SP + bpos(warp * 8 + g) * 2;
        auto k_tiles = [&](int n) {
#pragma unroll 1
            for (int i = 0; i < n; i++) {
                const uint32_t base = st * TILE_BYTES;
                mbar_wait(bar_full + st * 8, ph);
                uint32_t k0[4], k1[4], k2[4], k3[4];
                ldsm4(k0, base + koff0); ldsm4(k1, base + koff1);
                ldsm4(k2, base + koff0 + 128); ldsm4(k3, base + koff1 + 128);
                float s0[4] = {0.f, 0.f, 0.f, 0.f}, s1[4] = {0.f, 0.f, 0.f, 0.f};
                mma_bf16(s0, qa[0], qa[2], qa[1], qa[3], k0[0], k0[1]);
                mma_bf16(s1, qa[0], qa[2], qa[1], qa[3], k0[2], k0[3]);
                mma_bf16(s0, qa[4], qa[6], qa[5], qa[7], k1[0], k1[1]);
                mma_bf16(s1, qa[4], qa[6], qa[5], qa[7], k1[2], k1[3]);
                mma_bf16(s0, qa[8], qa[10], qa[9], qa[11], k2[0], k2[1]);
                mma_bf16(s1, qa[8], qa[10], qa[9], qa[11], k2[2], k2[3]);
                mma_bf16(s0, qa[12], qa[14], qa[13], qa[15], k3[0], k3[1]);
                mma_bf16(s1, qa[12], qa[14], qa[13], qa[15], k3[2], k3[3]);
                __syncwarp();
                if (lane == 0) mbar_arrive(bar_empty + st * 8);
                const float raw = (g & 1) ? s0[1] + s1[3] : s0[0] + s1[2];
                const uint32_t sc = pack_bf(rnd_bf(raw) * 0.08838834764831845f, 0.f);
                if (valid) { sts16(spos, (uint16_t)sc); mx = fmaxf(mx, bf_lo(sc)); }
                spos += TILE_KEYS * 2;
                if (++st == NST) { st = 0; ph ^= 1; }
            }
        };
        k_tiles(KPRE);
        {
            static_assert(T_WO == NST, "wo tiles sit in slots 0..3, second pass");
            const int s = warp >> 1;
            const int row = (mi >> 1) * 4 + (rr >> 1) + (rr & 1) * 8;
            const uint32_t base = sb + OFF_RING + s * TILE_BYTES + row * 128;
            const uint32_t c0 = (((mi & 1) * 2 + (warp & 1)) ^ (row & 7)) * 16, c1 = c0 ^ 64;
            mbar_wait(bar_full + s * 8, 1);
#pragma unroll
            for (int t = 0; t < 8; t++) {
                ldsm4t(*(uint32_t(*)[4])(wf + 8 * t), base + t * 2048 + c0);
                ldsm4t(*(uint32_t(*)[4])(wf + 8 * t + 4), base + t * 2048 + c1);
            }
            __syncwarp();
            if (lane < 4) mbar_arrive(bar_empty + lane * 8);
            st = 4;
        }
        k_tiles(NTILE - KPRE);
    }
    {
#pragma unroll
        for (int o = 16; o; o >>= 1) mx = fmaxf(mx, __shfl_xor_sync(~0u, mx, o));
        if (lane == 0) sts32(sb + OFF_RED + warp * 4, __float_as_uint(mx));
        cons_sync();
        const uint4 m0 = lds128(sb + OFF_RED), m1 = lds128(sb + OFF_RED + 16);
        const float mloc = fmaxf(fmaxf(fmaxf(__uint_as_float(m0.x), __uint_as_float(m0.y)), fmaxf(__uint_as_float(m0.z), __uint_as_float(m0.w))),
                                 fmaxf(fmaxf(__uint_as_float(m1.x), __uint_as_float(m1.y)), fmaxf(__uint_as_float(m1.z), __uint_as_float(m1.w))));
        const uint4 s0 = lds128(sb + OFF_SP + tid * 16), s1 = lds128(sb + OFF_SP + 4096 + tid * 16);
        const uint32_t sv[8] = {s0.x, s0.y, s0.z, s0.w, s1.x, s1.y, s1.z, s1.w};
        constexpr float LOG2E = 1.4426950408889634f;
        float l = 0.f;
#pragma unroll
        for (int i = 0; i < 8; i++) l += exp2f((bf_lo(sv[i]) - mloc) * LOG2E) + exp2f((bf_hi(sv[i]) - mloc) * LOG2E);
#pragma unroll
        for (int o = 16; o; o >>= 1) l += __shfl_xor_sync(~0u, l, o);
        if (lane == 0) sts32(sb + OFF_RED + 32 + warp * 4, __float_as_uint(l));
        cons_sync();
        const uint4 l0 = lds128(sb + OFF_RED + 32), l1 = lds128(sb + OFF_RED + 48);
        const float lloc = ((__uint_as_float(l0.x) + __uint_as_float(l0.y)) + (__uint_as_float(l0.z) + __uint_as_float(l0.w))) +
                           ((__uint_as_float(l1.x) + __uint_as_float(l1.y)) + (__uint_as_float(l1.z) + __uint_as_float(l1.w)));
        if (tid == 0) st_async_v2(mapa(sb + OFF_ML, rank ^ 1), __float_as_uint(mloc), __float_as_uint(lloc), mapa(bar_ml, rank ^ 1));
        mbar_wait(bar_ml, 0);
        const uint2 pml = lds64(sb + OFF_ML);
        const float mp = __uint_as_float(pml.x), lp = __uint_as_float(pml.y);
        const float M = fmaxf(mloc, mp);
        const float m_a = rank ? mp : mloc, l_a = rank ? lp : lloc, m_b = rank ? mloc : mp, l_b = rank ? lloc : lp;
        const float L = l_a * exp2f((m_a - M) * LOG2E) + l_b * exp2f((m_b - M) * LOG2E);
        const float inv = 1.0f / L;
        uint32_t pv[8];
#pragma unroll
        for (int i = 0; i < 8; i++)
            pv[i] = pack_bf(exp2f((bf_lo(sv[i]) - M) * LOG2E) * inv, exp2f((bf_hi(sv[i]) - M) * LOG2E) * inv);
        sts128(sb + OFF_SP + tid * 16, make_uint4(pv[0], pv[1], pv[2], pv[3]));
        sts128(sb + OFF_SP + 4096 + tid * 16, make_uint4(pv[4], pv[5], pv[6], pv[7]));
        cons_sync();
    }
    unsigned long long* acc1_dst = g_acc1 + b * D_MODEL + rank * 256 + warp * 32 + c * 8 + g;
    uint32_t o_dst = sb + OFF_O + (rank * 2 + (c & 1)) * O_STRIDE + (warp * 8 + g) * 4, o_bar = bar_o;
    if (c & 2) { o_dst = mapa(o_dst, rank ^ 1); o_bar = mapa(bar_o, rank ^ 1); }
    uint32_t o_src = sb + OFF_O + (rr & 3) * O_STRIDE + mi * 16;
    unsigned* tick_dst = g_tick + (bh & 7) * 32;
    asm volatile("" : "+l"(acc1_dst), "+l"(tick_dst), "+r"(o_dst), "+r"(o_bar), "+r"(o_src));
    const bool is_fin = bh < NFIN;
    const unsigned long long* p1 = g_acc1 + mb_ * D_MODEL + warp * 64 + j4 * 8 + c * 2;
    uint4* part_dst = g_part + ((warp * 4 + c) * NMLP + bh) * 8 + g;
    const uint4* inbox = g_part + bh * (NMLP * 8) + tid;
    const uint4* inbox2 = tid < (NMLP - 32) * 8 ? inbox + 256 : inbox;
    const uint4* inbox_pf = g_part + (bh * NMLP + tid) * 8;
    int do_pf = is_fin && tid < NMLP;
    float wsel = tid < (NMLP - 32) * 8 ? 1.0f : 0.0f;
    __nv_bfloat16* out_dst = out + ((lane >> 3) & 1) * D_MODEL + bh * 16 + (lane >> 4) * 8 + (lane & 7);
    asm volatile("" : "+l"(p1), "+l"(part_dst), "+l"(inbox), "+l"(inbox2), "+l"(inbox_pf), "+r"(do_pf), "+f"(wsel), "+l"(out_dst));
    uint32_t xv[2] = {lds32(sb + OFF_X + (mb_ * D_MODEL + d0) * 2), lds32(sb + OFF_X + (mb_ * D_MODEL + d0 + 8) * 2)};
    float b1v = bf16_at(sb + OFF_X + 3072 + lane * 2);
    float b2v = bf16_at(sb + OFF_X + 2048 + ((bh & 31) * 16 + (lane >> 4) * 8 + (lane & 7)) * 2);
    uint32_t a_part = sb + OFF_PART + warp * 256 + ((c >> 1) * 32 + (c & 1) * 16 + g) * 4;
    uint32_t a_stat = sb + OFF_STAT + (mb_ * 16 + (c & 1) * 8 + warp) * 4;
    uint32_t a_keep = sb + OFF_RED + mb_ * 32 + c * 4;
    uint32_t a_sum = sb + OFF_PART + (warp * 32 + lane) * 4, a_cs = sb + OFF_CS + lane * 4;
    uint32_t a_hid = sb + OFF_HID + warp * 80 + lane * 2, a_hidb = sb + OFF_HID + (rr & 1) * 80 + mi * 16;
    uint32_t a_fin = sb + OFF_PART + warp * 256 + lane * 4;
    uint32_t a_hfin = sb + OFF_RED + ((lane >> 3) & 1) * 32 + ((lane >> 4) * 8 + (lane & 7)) * 2;
    int keep_h = warp * 4 + j4 == bh;
    asm volatile("" : "+r"(a_part), "+r"(a_stat), "+r"(a_keep), "+r"(a_sum), "+r"(a_cs), "+r"(a_hid), "+r"(a_hidb), "+r"(a_fin), "+r"(a_hfin),
                 "+r"(keep_h), "+f"(b1v), "+f"(b2v));
    static_assert(T_W1 % NST + 3 < NST, "w1/w2 occupy four consecutive slots with the same parity");
    constexpr int W_PAR = (T_W1 / NST) & 1;
    uint32_t w1_bar = bar_full + (T_W1 % NST + (warp >> 2)) * 8;
    uint32_t w1_a = sb + OFF_RING + (T_W1 % NST + (warp >> 2)) * TILE_BYTES + ((warp & 3) * 64 + (mi >> 1) * 8 + rr) * 64 + ((mi & 1) ^ (rr >> 1)) * 16;
    uint32_t w2_a = sb + OFF_RING + (T_W2 % NST + (warp >> 2)) * TILE_BYTES + (warp & 3) * 4096 + ((mi >> 1) * 8 + rr) * 128 + ((mi & 1) ^ rr) * 16;
    asm volatile("" : "+r"(w1_bar), "+r"(w1_a), "+r"(w2_a));
    {
        const int hh = warp >> 2, ch = 2 * (warp & 3);
        const int line = 2 * (8 * (mi >> 1) + rr) + hh;
        uint32_t voff = sb + OFF_RING + line * 128 + (((ch ^ (mi & 1) ^ (rr >> 2)) ^ (line & 7)) * 16);
        uint32_t pmask = ((c >> 1) == (g & 1)) ? 0xffffffffu : 0u;
        asm volatile("" : "+r"(voff), "+r"(pmask));
        uint32_t paddr = sb + OFF_SP + c * 32;
        float o0[4] = {0.f, 0.f, 0.f, 0.f}, o1[4] = {0.f, 0.f, 0.f, 0.f};
#pragma unroll 1
        for (int i = 0; i < NTILE; i++) {
            const uint32_t base = voff + st * TILE_BYTES;
            uint4 p0 = lds128(paddr), p1 = lds128(paddr + 16);
            p0.x &= pmask; p0.y &= pmask; p0.z &= pmask; p0.w &= pmask;
            p1.x &= pmask; p1.y &= pmask; p1.z &= pmask; p1.w &= pmask;
            asm volatile("" : "+r"(p0.x), "+r"(p0.y), "+r"(p0.z), "+r"(p0.w), "+r"(p1.x), "+r"(p1.y), "+r"(p1.z), "+r"(p1.w));
            mbar_wait(bar_full + st * 8, ph);
            uint32_t a0[4], a1[4], a2[4], a3[4];
            ldsm4t(a0, base); ldsm4t(a1, base + 4096); ldsm4t(a2, base + 8192); ldsm4t(a3, base + 12288);
            if (i == NTILE - 1 && tid == 0) {
                asm volatile("red.relaxed.gpu.global.add.u32 [%0], 1;" ::"l"(tick_dst) : "memory");
                mbar_arrive(bar_end);
            }
            mma_bf16(o0, a0[0], a0[1], a0[2], a0[3], p0.x, p0.y);
            mma_bf16(o1, a1[0], a1[1], a1[2], a1[3], p0.z, p0.w);
            mma_bf16(o0, a2[0], a2[1], a2[2], a2[3], p1.x, p1.y);
            mma_bf16(o1, a3[0], a3[1], a3[2], a3[3], p1.z, p1.w);
            __syncwarp();
            if (lane == 0) mbar_arrive(bar_empty + st * 8);
            paddr += TILE_KEYS * 2;
            if (++st == NST) { st = 0; ph ^= 1; }
        }
        const float v0 = (o0[0] + o1[0]) + (o0[3] + o1[3]);
        const float v1 = (o0[1] + o1[1]) + (o0[2] + o1[2]);
        const uint32_t hi = pack_bf(v0, v1);
        const uint32_t val = (c & 1) ? pack_bf(v0 - bf_lo(hi), v1 - bf_hi(hi)) : hi;
        if (c & 2) st_async_b32(o_dst, val, o_bar);
        else sts32(o_dst, val);
        __syncwarp();
        if (lane == 0) mbar_arrive(bar_o);
        mbar_wait(bar_o, 0);
    }
    {
        float d00[4] = {0.f, 0.f, 0.f, 0.f}, d01[4] = {0.f, 0.f, 0.f, 0.f}, d10[4] = {0.f, 0.f, 0.f, 0.f}, d11[4] = {0.f, 0.f, 0.f, 0.f};
        uint32_t ob[4][4];
#pragma unroll
        for (int t = 0; t < 4; t++) ldsm4(ob[t], o_src + t * 64);
#pragma unroll
        for (int t = 0; t < 4; t++) {
            mma_bf16(d00, wf[16 * t], wf[16 * t + 1], wf[16 * t + 2], wf[16 * t + 3], ob[t][0], ob[t][1]);
            mma_bf16(d10, wf[16 * t + 4], wf[16 * t + 5], wf[16 * t + 6], wf[16 * t + 7], ob[t][0], ob[t][1]);
            mma_bf16(d01, wf[16 * t + 8], wf[16 * t + 9], wf[16 * t + 10], wf[16 * t + 11], ob[t][2], ob[t][3]);
            mma_bf16(d11, wf[16 * t + 12], wf[16 * t + 13], wf[16 * t + 14], wf[16 * t + 15], ob[t][2], ob[t][3]);
        }
        const float e0 = (d00[0] + d01[0]) + (d00[1] + d01[1]), e1 = (d00[2] + d01[2]) + (d00[3] + d01[3]);
        const float e2 = (d10[0] + d11[0]) + (d10[1] + d11[1]), e3 = (d10[2] + d11[2]) + (d10[3] + d11[3]);
        const float ea = (c & 2) ? e2 : e0, eb = (c & 2) ? e3 : e1;
        const float e = ((c & 1) ? eb : ea) + __shfl_xor_sync(~0u, (c & 1) ? ea : eb, 1);
        red_add64(acc1_dst, fx_encode(e));
    }
    if (!is_mlp) return;

    {
        if (do_pf) asm volatile("prefetch.global.L2 [%0];" ::"l"(inbox_pf));
        uint32_t* a1 = wf;
        uint32_t* a2 = wf + 32;
        auto load_w1 = [&]() {
#pragma unroll
            for (int k = 0; k < 4; k++) {
                ldsm4t(*(uint32_t(*)[4])(a1 + 8 * k), w1_a + k * 1024);
                ldsm4t(*(uint32_t(*)[4])(a1 + 8 * k + 4), (w1_a ^ 32) + k * 1024);
            }
        };
        auto load_w2 = [&]() {
#pragma unroll
            for (int u = 0; u < 2; u++)
#pragma unroll
                for (int T = 0; T < 4; T++) ldsm4t(*(uint32_t(*)[4])(a2 + 16 * u + 4 * T), (w2_a ^ (T * 32)) + u * 2048);
        };
        uint32_t hb0, hb1;
        int stage = 0;
        {
            uint4 ua = make_uint4(0, 0, 0, 0), ub = ua;
            int n = 0, polled = 0;
#pragma unroll 1
            do {
                if (!polled && __all_sync(~0u, mbar_test(bar_go, 0))) {
                    ld_relaxed2x64(ua, p1); ld_relaxed2x64(ub, p1 + 32);
                    polled = 1;
                }
                if (stage < 2 && __all_sync(~0u, mbar_test(w1_bar + stage * 16, W_PAR))) {
                    if (stage == 0) load_w1(); else load_w2();
                    stage++;
                }
                if (++n > SPIN_LIMIT * 16) __trap();
            } while (stage < 1 || !polled);
            if (stage < 2 && __all_sync(~0u, mbar_test(w1_bar + 16, W_PAR))) { load_w2(); stage = 2; }
            n = 0;
            while (!all_complete(ua, ub)) {
                ld_relaxed2x64(ua, p1); ld_relaxed2x64(ub, p1 + 32);
                if (++n > SPIN_LIMIT) __trap();
            }
            const uint32_t at0 = pack_bf(fx_decode(ua.x, ua.y), fx_decode(ua.z, ua.w)), at1 = pack_bf(fx_decode(ub.x, ub.y), fx_decode(ub.z, ub.w));
            hb0 = pack_bf(bf_lo(xv[0]) + bf_lo(at0), bf_hi(xv[0]) + bf_hi(at0));
            hb1 = pack_bf(bf_lo(xv[1]) + bf_lo(at1), bf_hi(xv[1]) + bf_hi(at1));
        }
        gemv1_partial(a1, hb0, hb1, j4, c, a_part);
        {
            const float h0 = bf_lo(hb0), h1 = bf_hi(hb0), h2 = bf_lo(hb1), h3 = bf_hi(hb1);
            const float s1 = (h0 + h1) + (h2 + h3);
            const float s2 = (h0 * h0 + h1 * h1) + (h2 * h2 + h3 * h3);
            float t = ((c & 1) ? s2 : s1) + __shfl_xor_sync(~0u, (c & 1) ? s1 : s2, 1);
            t += __shfl_xor_sync(~0u, t, 2);
            t += __shfl_xor_sync(~0u, t, 8);
            t += __shfl_xor_sync(~0u, t, 16);
            if ((lane & 0x1a) == 0) sts32(a_stat, __float_as_uint(t));
        }
        if (keep_h) {
            sts32(a_keep, hb0);
            sts32(a_keep + 16, hb1);
        }
        asm volatile("bar.sync 2, 288;" ::: "memory");
        if (warp < 2) {
            const uint4 q0 = lds128(sb + OFF_STAT + warp * 64), q1 = lds128(sb + OFF_STAT + warp * 64 + 16);
            const uint4 q2 = lds128(sb + OFF_STAT + warp * 64 + 32), q3 = lds128(sb + OFF_STAT + warp * 64 + 48);
            const float sacc = sum8(a_sum);
            const float cs = __uint_as_float(lds32(a_cs));
            const float mean = (((__uint_as_float(q0.x) + __uint_as_float(q0.y)) + (__uint_as_float(q0.z) + __uint_as_float(q0.w))) +
                                ((__uint_as_float(q1.x) + __uint_as_float(q1.y)) + (__uint_as_float(q1.z) + __uint_as_float(q1.w)))) * (1.0f / D_MODEL);
            const float msq = (((__uint_as_float(q2.x) + __uint_as_float(q2.y)) + (__uint_as_float(q2.z) + __uint_as_float(q2.w))) +
                               ((__uint_as_float(q3.x) + __uint_as_float(q3.y)) + (__uint_as_float(q3.z) + __uint_as_float(q3.w)))) * (1.0f / D_MODEL);
            const float var = fmaxf(msq - mean * mean, 0.f);
            float sq, iden;
            asm("sqrt.approx.ftz.f32 %0, %1;" : "=f"(sq) : "f"(rnd_bf(rnd_bf(var) + 1e-5f)));
            asm("rcp.approx.ftz.f32 %0, %1;" : "=f"(iden) : "f"(rnd_bf(sq)));
            const float z = fmaxf(rnd_bf(rnd_bf((sacc - rnd_bf(mean) * cs) * iden) + b1v), 0.f);
            sts16(a_hid, (uint16_t)pack_bf(z * z, 0.f));
        }
        if (stage < 2) { mbar_wait(w1_bar + 16, W_PAR); load_w2(); }
        cons_sync();
        uint32_t hb[4];
        ldsm4(hb, a_hidb);
        const float hfin = bf16_at(a_hfin);
        float y[4][4];
#pragma unroll
        for (int T = 0; T < 4; T++) {
            y[T][0] = y[T][1] = y[T][2] = y[T][3] = 0.f;
            mma_bf16(y[T], a2[4 * T], a2[4 * T + 1], a2[4 * T + 2], a2[4 * T + 3], hb[0], hb[1]);
        }
#pragma unroll
        for (int T = 0; T < 4; T++)
            mma_bf16(y[T], a2[16 + 4 * T], a2[16 + 4 * T + 1], a2[16 + 4 * T + 2], a2[16 + 4 * T + 3], hb[2], hb[3]);
        {
            const bool up2 = c & 2, up1 = c & 1;
            uint32_t e[4];
#pragma unroll
            for (int i = 0; i < 4; i++) e[i] = __float_as_uint(up2 ? (up1 ? y[3][i] : y[2][i]) : (up1 ? y[1][i] : y[0][i])) | 1u;
            asm volatile("st.relaxed.gpu.global.v4.u32 [%0], {%1,%2,%3,%4};" ::"l"(part_dst), "r"(e[0]), "r"(e[1]), "r"(e[2]), "r"(e[3]) : "memory");
        }
        if (!is_fin) return;
        {
            uint4 u, w;
            int n = 0;
            spin_cycles(DELAY2);
            do {
                ld_relaxed128(u, inbox); ld_relaxed128(w, inbox2);
                if (++n > SPIN_LIMIT) __trap();
            } while (!all_marked(u, w));
            const float v0 = fmaf(__uint_as_float(w.x), wsel, __uint_as_float(u.x)), v1 = fmaf(__uint_as_float(w.y), wsel, __uint_as_float(u.y));
            const float v2 = fmaf(__uint_as_float(w.z), wsel, __uint_as_float(u.z)), v3 = fmaf(__uint_as_float(w.w), wsel, __uint_as_float(u.w));
            const bool up16 = lane & 16, up8 = lane & 8;
            const float r0 = (up16 ? v2 : v0) + __shfl_xor_sync(~0u, up16 ? v0 : v2, 16);
            const float r1 = (up16 ? v3 : v1) + __shfl_xor_sync(~0u, up16 ? v1 : v3, 16);
            const float r = (up8 ? r1 : r0) + __shfl_xor_sync(~0u, up8 ? r0 : r1, 8);
            sts32(a_fin, __float_as_uint(r));
        }
        cons_sync();
        if (warp == 0) {
            const float y2 = sum8(a_sum);
            *out_dst = __ushort_as_bfloat16((unsigned short)pack_bf(hfin + rnd_bf(rnd_bf(y2) + b2v), 0.f));
        }
        if (bh == 0) {
            *(ulonglong2*)(g_acc1 + tid * 4) = make_ulonglong2(0, 0);
            *(ulonglong2*)(g_acc1 + tid * 4 + 2) = make_ulonglong2(0, 0);
            if (tid < 8) g_tick[tid * 32] = 0;
        }
    }
}

typedef CUresult (*EncodeFn)(CUtensorMap*, CUtensorMapDataType, cuuint32_t, void*, const cuuint64_t*, const cuuint64_t*,
                             const cuuint32_t*, const cuuint32_t*, CUtensorMapInterleave, CUtensorMapSwizzle,
                             CUtensorMapL2promotion, CUtensorMapFloatOOBfill);

void make_map(EncodeFn enc, CUtensorMap* tm, void* ptr, uint64_t cols, uint64_t rows, uint32_t box_cols, uint32_t box_rows,
              CUtensorMapSwizzle swz) {
    const cuuint64_t dims[2] = {cols, rows};
    const cuuint64_t strides[1] = {cols * 2};
    const cuuint32_t box[2] = {box_cols, box_rows};
    const cuuint32_t es[2] = {1, 1};
    enc(tm, CU_TENSOR_MAP_DATA_TYPE_BFLOAT16, 2, ptr, dims, strides, box, es, CU_TENSOR_MAP_INTERLEAVE_NONE, swz,
        CU_TENSOR_MAP_L2_PROMOTION_NONE, CU_TENSOR_MAP_FLOAT_OOB_FILL_NONE);
}

}

extern "C" void kernel_launch(void* const* d_in, const int* in_sizes, int n_in, void* d_out, int out_size) {
    (void)in_sizes; (void)n_in; (void)out_size;
    static EncodeFn enc = nullptr;
    static Scratch* scr = nullptr;
    static uint32_t tile_ns_x16 = 0;
    if (!enc) {
        void* fn = nullptr;
        cudaDriverEntryPointQueryResult qr;
        cudaGetDriverEntryPoint("cuTensorMapEncodeTiled", &fn, cudaEnableDefault, &qr);
        enc = (EncodeFn)fn;
        cudaGetSymbolAddress((void**)&scr, g_scratch);
        int dev = 0, mem_khz = 0, bus_bits = 0;
        cudaGetDevice(&dev);
        cudaDeviceGetAttribute(&mem_khz, cudaDevAttrMemoryClockRate, dev);
        cudaDeviceGetAttribute(&bus_bits, cudaDevAttrGlobalMemoryBusWidth, dev);
        const double bytes_per_ns = 2.0 * mem_khz * 1e-6 * (bus_bits / 8) * (PACE * 1e-3);
        if (bytes_per_ns > 0) tile_ns_x16 = (uint32_t)(16.0 * NCTA * TILE_BYTES / bytes_per_ns);
        cudaFuncSetAttribute(decode_block_kernel, cudaFuncAttributeMaxDynamicSharedMemorySize, SMEM_BYTES);
    }
    Maps tm;
    make_map(enc, &tm.v, d_in[2], 64, (uint64_t)2 * NHEAD * SK * 2, 64, TILE_KEYS * 2, CU_TENSOR_MAP_SWIZZLE_128B);
    make_map(enc, &tm.wq, d_in[3], QCOLS, D_MODEL, 64, 128, CU_TENSOR_MAP_SWIZZLE_128B);
    make_map(enc, &tm.wo, d_in[4], D_MODEL, QCOLS, 64, 128, CU_TENSOR_MAP_SWIZZLE_128B);
    make_map(enc, &tm.w1, d_in[6], FF, D_MODEL, 32, 256, CU_TENSOR_MAP_SWIZZLE_64B);
    make_map(enc, &tm.w2, d_in[8], D_MODEL, FF, 64, 32, CU_TENSOR_MAP_SWIZZLE_128B);
    decode_block_kernel<<<NCTA, NTHREADS, SMEM_BYTES>>>(
        tm, (const __nv_bfloat16*)d_in[0], (const __nv_bfloat16*)d_in[1], (const __nv_bfloat16*)d_in[7],
        (const __nv_bfloat16*)d_in[9], (__nv_bfloat16*)d_out, scr, tile_ns_x16);
}
```

```cpp
#include <cuda_runtime.h>
#include <cuda_bf16.h>
#include <cuda.h>
#include <stdint.h>

namespace {

constexpr int D_MODEL = 512;
constexpr int NHEAD = 32;
constexpr int SK = 8192;
constexpr int DH = 128;
constexpr int FF = 1376;
constexpr int QCOLS = NHEAD * DH;

constexpr int NCTA = 128;
constexpr int KEYS_PER_CTA = SK / 2;
constexpr int TILE_KEYS = 64;
constexpr int TILE_BYTES = TILE_KEYS * DH * 2;
constexpr int NTILE = KEYS_PER_CTA / TILE_KEYS;
constexpr int NST = 12;
constexpr int NINIT = 5;
constexpr int WLATE = 1;
constexpr int LEAD = 7;
constexpr int PACE = 958;
constexpr int SKEW = 8;
constexpr int DELAY2 = 300;
constexpr int NCONS = 256;
constexpr int NTHREADS = NCONS + 64;
constexpr int NMLP = FF / 32;
constexpr int KPRE = NST - 4;
constexpr int T_WQ = 0, T_K0 = 4, T_WO = T_K0 + KPRE, T_K1 = T_WO + 4, T_V = T_K1 + NTILE - KPRE, T_W1 = T_V + NTILE,
              T_W2 = T_W1 + 2, T_END = T_W2 + 2;

constexpr int OFF_RING = 0;
constexpr int OFF_SP = OFF_RING + NST * TILE_BYTES;
constexpr int OFF_PART = OFF_SP + KEYS_PER_CTA * 2;
constexpr int OFF_CS = OFF_PART + 8 * 64 * 4;
constexpr int OFF_XN = OFF_CS + 32 * 4;
constexpr int OFF_X = OFF_XN + 1024;
constexpr int O_STRIDE = 272;
constexpr int OFF_O = OFF_X + 2048 + 1024 + 64;
constexpr int OFF_Q = OFF_O + 4 * O_STRIDE;
constexpr int OFF_RED = OFF_Q + 256;
constexpr int OFF_STAT = OFF_RED + 64;
constexpr int OFF_HID = OFF_STAT + 128;
constexpr int OFF_ML = OFF_HID + 160;
constexpr int OFF_BAR = OFF_ML + 16;
constexpr int SMEM_USED = OFF_BAR + (2 * NST + 5) * 8;
constexpr int SMEM_BYTES = SMEM_USED + 1024;

constexpr float FX_SCALE = 1073741824.0f;
constexpr float FX_INV = 1.0f / 1073741824.0f;

constexpr int NFIN = 32;
struct Scratch {
    unsigned long long acc1[2 * D_MODEL];
    unsigned int tick[8 * 32];
    uint4 part[NFIN * NMLP * 8];
};
__device__ __align__(1024) Scratch g_scratch;

__device__ __forceinline__ void mbar_init(uint32_t bar, uint32_t cnt) {
    asm volatile("mbarrier.init.shared::cta.b64 [%0], %1;" ::"r"(bar), "r"(cnt) : "memory");
}
__device__ __forceinline__ void mbar_expect_tx(uint32_t bar, uint32_t bytes) {
    asm volatile("mbarrier.arrive.expect_tx.shared::cta.b64 _, [%0], %1;" ::"r"(bar), "r"(bytes) : "memory");
}
__device__ __forceinline__ void mbar_arrive(uint32_t bar) {
    asm volatile("mbarrier.arrive.shared::cta.b64 _, [%0];" ::"r"(bar) : "memory");
}
__device__ __forceinline__ bool mbar_test(uint32_t bar, uint32_t parity) {
    uint32_t ok;
    asm volatile("{\n.reg .pred p;\nmbarrier.test_wait.parity.shared::cta.b64 p, [%1], %2;\nselp.u32 %0, 1, 0, p;\n}"
                 : "=r"(ok) : "r"(bar), "r"(parity) : "memory");
    return ok;
}
__device__ __forceinline__ bool mbar_try(uint32_t bar, uint32_t parity) {
    uint32_t ok;
    asm volatile("{\n.reg .pred p;\nmbarrier.try_wait.parity.shared::cta.b64 p, [%1], %2;\nselp.u32 %0, 1, 0, p;\n}"
                 : "=r"(ok) : "r"(bar), "r"(parity) : "memory");
    return ok;
}
constexpr int SPIN_LIMIT = 1 << 20;
__device__ __forceinline__ void mbar_wait(uint32_t bar, uint32_t parity) {
    int n = 0;
    while (!mbar_try(bar, parity)) { if (++n > SPIN_LIMIT) __trap(); }
}
__device__ __forceinline__ void bulk_load(uint32_t dst, const void* src, uint32_t bytes, uint32_t bar) {
    asm volatile("cp.async.bulk.shared::cluster.global.mbarrier::complete_tx::bytes [%0], [%1], %2, [%3];"
                 ::"r"(dst), "l"(src), "r"(bytes), "r"(bar) : "memory");
}
__device__ __forceinline__ void tma2d(uint32_t dst, const CUtensorMap* tm, int c0, int c1, uint32_t bar) {
    asm volatile("cp.async.bulk.tensor.2d.shared::cluster.global.mbarrier::complete_tx::bytes [%0], [%1, {%3, %4}], [%2];"
                 ::"r"(dst), "l"(tm), "r"(bar), "r"(c0), "r"(c1) : "memory");
}
__device__ __forceinline__ void bulk_load_stream(uint32_t dst, const void* src, uint32_t bytes, uint32_t bar, uint64_t pol) {
    asm volatile("cp.async.bulk.shared::cluster.global.mbarrier::complete_tx::bytes.L2::cache_hint [%0], [%1], %2, [%3], %4;"
                 ::"r"(dst), "l"(src), "r"(bytes), "r"(bar), "l"(pol) : "memory");
}
__device__ __forceinline__ void tma2d_stream(uint32_t dst, const CUtensorMap* tm, int c0, int c1, uint32_t bar, uint64_t pol) {
    asm volatile("cp.async.bulk.tensor.2d.shared::cluster.global.mbarrier::complete_tx::bytes.L2::cache_hint [%0], [%1, {%3, %4}], [%2], %5;"
                 ::"r"(dst), "l"(tm), "r"(bar), "r"(c0), "r"(c1), "l"(pol) : "memory");
}
__device__ __forceinline__ bool elect_one() {
    uint32_t p;
    asm volatile("{\n.reg .pred p;\nelect.sync _|p, 0xffffffff;\nselp.u32 %0, 1, 0, p;\n}" : "=r"(p));
    return p;
}
__device__ __forceinline__ void cons_sync() { asm volatile("bar.sync 1, 256;" ::: "memory"); }

__device__ __forceinline__ uint32_t mapa(uint32_t addr, uint32_t rank) {
    uint32_t r;
    asm("mapa.shared::cluster.u32 %0, %1, %2;" : "=r"(r) : "r"(addr), "r"(rank));
    return r;
}
__device__ __forceinline__ void st_async_b32(uint32_t addr, uint32_t v, uint32_t bar) {
    asm volatile("st.async.weak.shared::cluster.mbarrier::complete_tx::bytes.b32 [%0], %1, [%2];" ::"r"(addr), "r"(v), "r"(bar) : "memory");
}
__device__ __forceinline__ void st_async_v2(uint32_t addr, uint32_t v0, uint32_t v1, uint32_t bar) {
    asm volatile("st.async.weak.shared::cluster.mbarrier::complete_tx::bytes.v2.b32 [%0], {%1, %2}, [%3];" ::"r"(addr), "r"(v0), "r"(v1), "r"(bar) : "memory");
}

__device__ __forceinline__ void mma_bf16(float (&d)[4], uint32_t a0, uint32_t a1, uint32_t a2, uint32_t a3, uint32_t b0, uint32_t b1) {
    asm volatile("mma.sync.aligned.m16n8k16.row.col.f32.bf16.bf16.f32 {%0,%1,%2,%3}, {%4,%5,%6,%7}, {%8,%9}, {%0,%1,%2,%3};"
                 : "+f"(d[0]), "+f"(d[1]), "+f"(d[2]), "+f"(d[3])
                 : "r"(a0), "r"(a1), "r"(a2), "r"(a3), "r"(b0), "r"(b1));
}
__device__ __forceinline__ void ldsm4(uint32_t (&r)[4], uint32_t addr) {
    asm volatile("ldmatrix.sync.aligned.m8n8.x4.shared.b16 {%0,%1,%2,%3}, [%4];"
                 : "=r"(r[0]), "=r"(r[1]), "=r"(r[2]), "=r"(r[3]) : "r"(addr) : "memory");
}
__device__ __forceinline__ void ldsm4t(uint32_t (&r)[4], uint32_t addr) {
    asm volatile("ldmatrix.sync.aligned.m8n8.x4.trans.shared.b16 {%0,%1,%2,%3}, [%4];"
                 : "=r"(r[0]), "=r"(r[1]), "=r"(r[2]), "=r"(r[3]) : "r"(addr) : "memory");
}
__device__ __forceinline__ uint4 lds128(uint32_t a) {
    uint4 v;
    asm volatile("ld.shared.v4.u32 {%0,%1,%2,%3}, [%4];" : "=r"(v.x), "=r"(v.y), "=r"(v.z), "=r"(v.w) : "r"(a) : "memory");
    return v;
}
__device__ __forceinline__ uint2 lds64(uint32_t a) {
    uint2 v;
    asm volatile("ld.shared.v2.u32 {%0,%1}, [%2];" : "=r"(v.x), "=r"(v.y) : "r"(a) : "memory");
    return v;
}
__device__ __forceinline__ uint32_t lds32(uint32_t a) {
    uint32_t v;
    asm volatile("ld.shared.u32 %0, [%1];" : "=r"(v) : "r"(a) : "memory");
    return v;
}
__device__ __forceinline__ void sts128(uint32_t a, uint4 v) {
    asm volatile("st.shared.v4.u32 [%0], {%1,%2,%3,%4};" ::"r"(a), "r"(v.x), "r"(v.y), "r"(v.z), "r"(v.w) : "memory");
}
__device__ __forceinline__ void sts64(uint32_t a, uint32_t v0, uint32_t v1) {
    asm volatile("st.shared.v2.u32 [%0], {%1,%2};" ::"r"(a), "r"(v0), "r"(v1) : "memory");
}
__device__ __forceinline__ void sts32(uint32_t a, uint32_t v) {
    asm volatile("st.shared.u32 [%0], %1;" ::"r"(a), "r"(v) : "memory");
}
__device__ __forceinline__ void sts16(uint32_t a, uint16_t v) {
    asm volatile("st.shared.u16 [%0], %1;" ::"r"(a), "h"(v) : "memory");
}
__device__ __forceinline__ float bf_lo(uint32_t v) { return __uint_as_float(v << 16); }
__device__ __forceinline__ float bf_hi(uint32_t v) { return __uint_as_float(v & 0xffff0000u); }
__device__ __forceinline__ uint32_t pack_bf(float lo, float hi) {
    uint32_t r;
    asm("cvt.rn.bf16x2.f32 %0, %1, %2;" : "=r"(r) : "f"(hi), "f"(lo));
    return r;
}
__device__ __forceinline__ float rnd_bf(float v) { return bf_lo(pack_bf(v, 0.f)); }

__device__ __forceinline__ unsigned long long fx_encode(float v) {
    return ((unsigned long long)__float2ll_rn(v * FX_SCALE) << 8) + 1ull;
}
__device__ __forceinline__ float fx_decode(uint32_t lo, uint32_t hi) {
    return fmaf(__int2float_rn((int)hi), 1.0f / 64.0f, __uint2float_rn(lo & 0xffffff00u) * (FX_INV / 256.0f));
}
__device__ __forceinline__ uint32_t gtime32() {
    uint32_t t;
    asm volatile("mov.u32 %0, %%globaltimer_lo;" : "=r"(t));
    return t;
}
__device__ __forceinline__ void wait_until(uint32_t t0, uint32_t ns) {
    for (int n = 0; gtime32() - t0 < ns && n < SPIN_LIMIT; n++) {}
}
__device__ __forceinline__ void spin_cycles(uint32_t n) {
    uint32_t t0, t;
    asm volatile("mov.u32 %0, %%clock;" : "=r"(t0));
    do { asm volatile("mov.u32 %0, %%clock;" : "=r"(t)); } while (t - t0 < n);
}
__device__ __forceinline__ void red_add64(unsigned long long* p, unsigned long long v) {
    asm volatile("red.relaxed.gpu.global.add.u64 [%0], %1;" ::"l"(p), "l"(v) : "memory");
}
__device__ __forceinline__ void ld_relaxed2x64(uint4& v, const void* p) {
    asm volatile("{\n.reg .b64 a, b;\nld.relaxed.gpu.global.v2.b64 {a, b}, [%4];\nmov.b64 {%0, %1}, a;\nmov.b64 {%2, %3}, b;\n}"
                 : "=r"(v.x), "=r"(v.y), "=r"(v.z), "=r"(v.w) : "l"(p) : "memory");
}
__device__ __forceinline__ void ld_relaxed128(uint4& v, const uint4* p) {
    asm volatile("ld.relaxed.gpu.global.v4.u32 {%0,%1,%2,%3}, [%4];" : "=r"(v.x), "=r"(v.y), "=r"(v.z), "=r"(v.w) : "l"(p) : "memory");
}
__device__ __forceinline__ uint32_t and3(uint32_t a, uint32_t b, uint32_t c) {
    uint32_t r;
    asm("lop3.b32 %0, %1, %2, %3, 0x80;" : "=r"(r) : "r"(a), "r"(b), "r"(c));
    return r;
}
__device__ __forceinline__ bool all_marked(const uint4& a, const uint4& b) {
    return __all_sync(~0u, and3(and3(a.x, a.y, a.z), and3(a.w, b.x, b.y), and3(b.z, b.w, 1u)));
}
__device__ __forceinline__ bool all_complete(const uint4& a, const uint4& b) {
    return __all_sync(~0u, and3(and3(a.x, a.z, b.x), b.z, 32u));
}
__device__ __forceinline__ float bf16_at(uint32_t a) {
    uint16_t v;
    asm volatile("ld.shared.u16 %0, [%1];" : "=h"(v) : "r"(a) : "memory");
    return __uint_as_float((uint32_t)v << 16);
}

__device__ __forceinline__ int bpos(int k) { return ((k >> 1) & 3) * 16 + ((k >> 4) & 3) * 4 + ((k >> 3) & 1) * 2 + (k & 1); }

__device__ __forceinline__ void gemv1_partial(const uint32_t* a1, uint32_t hb0, uint32_t hb1, int j, int c, uint32_t a) {
    float t0[4] = {0.f, 0.f, 0.f, 0.f}, t1[4] = {0.f, 0.f, 0.f, 0.f}, t2[4] = {0.f, 0.f, 0.f, 0.f}, t3[4] = {0.f, 0.f, 0.f, 0.f};
#pragma unroll
    for (int k = 0; k < 2; k++) {
        const uint32_t m0 = (j == k) ? hb0 : 0u, m1 = (j == k) ? hb1 : 0u;
        const uint32_t n0 = (j == k + 2) ? hb0 : 0u, n1 = (j == k + 2) ? hb1 : 0u;
        mma_bf16(t0, a1[8 * k], a1[8 * k + 1], a1[8 * k + 2], a1[8 * k + 3], m0, m1);
        mma_bf16(t1, a1[8 * k + 4], a1[8 * k + 5], a1[8 * k + 6], a1[8 * k + 7], m0, m1);
        mma_bf16(t2, a1[8 * k + 16], a1[8 * k + 17], a1[8 * k + 18], a1[8 * k + 19], n0, n1);
        mma_bf16(t3, a1[8 * k + 20], a1[8 * k + 21], a1[8 * k + 22], a1[8 * k + 23], n0, n1);
    }
    const bool up2 = c & 2, up1 = c & 1;
    float r4[4], r2[2];
    const float send[4] = {up2 ? t2[0] : t0[1], up2 ? t2[2] : t0[3], up2 ? t3[0] : t1[1], up2 ? t3[2] : t1[3]};
    const float keep[4] = {up2 ? t2[1] : t0[0], up2 ? t2[3] : t0[2], up2 ? t3[1] : t1[0], up2 ? t3[3] : t1[2]};
#pragma unroll
    for (int i = 0; i < 4; i++) r4[i] = keep[i] + __shfl_xor_sync(~0u, send[i], 2);
#pragma unroll
    for (int i = 0; i < 2; i++) r2[i] = (up1 ? r4[i + 2] : r4[i]) + __shfl_xor_sync(~0u, up1 ? r4[i] : r4[i + 2], 1);
    sts32(a, __float_as_uint(r2[0]));
    sts32(a + 32, __float_as_uint(r2[1]));
}

__device__ __forceinline__ float sum8(uint32_t a) {
    float p[8];
#pragma unroll
    for (int w = 0; w < 8; w++) p[w] = __uint_as_float(lds32(a + w * 256));
    return ((p[0] + p[1]) + (p[2] + p[3])) + ((p[4] + p[5]) + (p[6] + p[7]));
}

struct Maps { CUtensorMap v, wq, wo, w1, w2; };

__global__ void __cluster_dims__(2, 1, 1) __launch_bounds__(NTHREADS, 1)
decode_block_kernel(const __grid_constant__ Maps tm,
                    const __nv_bfloat16* __restrict__ x, const __nv_bfloat16* __restrict__ Kc,
                    const __nv_bfloat16* __restrict__ b1, const __nv_bfloat16* __restrict__ b2,
                    __nv_bfloat16* __restrict__ out, Scratch* __restrict__ scr, uint32_t tile_ns_x16) {
    unsigned long long* const g_acc1 = scr->acc1;
    unsigned int* const g_tick = scr->tick;
    uint4* const g_part = scr->part;
    extern __shared__ unsigned char smem_raw[];
    const uint32_t sb = ((uint32_t)__cvta_generic_to_shared(smem_raw) + 1023u) & ~1023u;
    const uint32_t bar_full = sb + OFF_BAR, bar_empty = bar_full + NST * 8;
    const uint32_t bar_q = bar_empty + NST * 8, bar_ml = bar_q + 8, bar_o = bar_ml + 8, bar_end = bar_o + 8, bar_go = bar_end + 8;

    const char* ksrc = (const char*)Kc + (size_t)blockIdx.x * (KEYS_PER_CTA * DH * 2);
    constexpr uint64_t pol = 0x12F0000000000000ull;
    if ((threadIdx.x & ~32) == 0) {
        const int k = threadIdx.x >> 5;
        mbar_init(bar_full + (T_K0 + k) * 8, 1);
        asm volatile("fence.mbarrier_init.release.cluster;" ::: "memory");
        mbar_expect_tx(bar_full + (T_K0 + k) * 8, TILE_BYTES);
        bulk_load_stream(sb + OFF_RING + (T_K0 + k) * TILE_BYTES, ksrc + k * TILE_BYTES, TILE_BYTES, bar_full + (T_K0 + k) * 8, pol);
    }
    int tid = threadIdx.x;
    asm volatile("" : "+r"(tid));
    const int lane = tid & 31;
    const int warp = __shfl_sync(~0u, tid >> 5, 0);
    const int bh = blockIdx.x >> 1, rank = blockIdx.x & 1;
    const int b = bh >> 5, h = bh & 31;
    const bool is_mlp = (rank == 0) && (bh < NMLP);
    const int f0 = bh * 32;

    if (elect_one()) {
        if (warp < 6) {
            if (warp >= 2) {
                const int s = T_WQ + warp - 2;
                mbar_init(bar_full + s * 8, 1);
                asm volatile("fence.mbarrier_init.release.cluster;" ::: "memory");
                mbar_expect_tx(bar_full + s * 8, TILE_BYTES);
                tma2d(sb + OFF_RING + s * TILE_BYTES, &tm.wq, h * DH + rank * 64, s * 128, bar_full + s * 8);
            }
        } else if (warp == 7) {
#pragma unroll
            for (int s = 0; s < NST; s++) mbar_init(bar_empty + s * 8, 8);
            asm volatile("fence.mbarrier_init.release.cluster;" ::: "memory");
        } else if (warp == 8) {
#pragma unroll
            for (int s = T_K0 + 2; s < NST; s++) mbar_init(bar_full + s * 8, 1);
            asm volatile("fence.mbarrier_init.release.cluster;" ::: "memory");
#pragma unroll
            for (int s = T_K0 + 2; s < T_K0 + NINIT; s++) {
                mbar_expect_tx(bar_full + s * 8, TILE_BYTES);
                bulk_load_stream(sb + OFF_RING + s * TILE_BYTES, ksrc + (size_t)(s - T_K0) * TILE_BYTES, TILE_BYTES, bar_full + s * 8, pol);
            }
        } else if (warp == 9) {
            mbar_init(bar_q, 2); mbar_init(bar_ml, 1); mbar_init(bar_o, 10); mbar_init(bar_end, 1); mbar_init(bar_go, 1);
            asm volatile("fence.mbarrier_init.release.cluster;" ::: "memory");
            mbar_expect_tx(bar_q, 128);
            mbar_expect_tx(bar_ml, is_mlp ? 8 + 2048 + 1024 + 64 : 8);
            if (is_mlp) {
                bulk_load(sb + OFF_X, x, 2048, bar_ml);
                bulk_load(sb + OFF_X + 2048, b2, 1024, bar_ml);
                bulk_load(sb + OFF_X + 3072, b1 + f0, 64, bar_ml);
            }
            mbar_expect_tx(bar_o, 512);
            asm volatile("prefetch.tensormap [%0];" ::"l"(&tm.wo) : "memory");
            asm volatile("prefetch.tensormap [%0];" ::"l"(&tm.v) : "memory");
            asm volatile("prefetch.tensormap [%0];" ::"l"(&tm.w1) : "memory");
            asm volatile("prefetch.tensormap [%0];" ::"l"(&tm.w2) : "memory");
        }
    }
    __syncwarp();
    asm volatile("barrier.cluster.arrive.relaxed.aligned;" ::: "memory");

    if (warp == 8) {
        const uint32_t t_start = gtime32();
        asm volatile("barrier.cluster.wait.aligned;" ::: "memory");
        if (lane == 0) {
#pragma unroll
            for (int w = 0; w < 4; w++) mbar_wait(bar_full + (T_WQ + w) * 8, 0);
#pragma unroll
            for (int k = NINIT; k < KPRE; k++) {
                const uint32_t fb = bar_full + (T_K0 + k) * 8;
                mbar_expect_tx(fb, TILE_BYTES);
                bulk_load_stream(sb + OFF_RING + (T_K0 + k) * TILE_BYTES, ksrc + (size_t)k * TILE_BYTES, TILE_BYTES, fb, pol);
            }
            const int vline0 = (bh * SK + rank * KEYS_PER_CTA) * 2;
            const int tend = is_mlp ? T_END : T_W1;
            const int lead16 = LEAD * 16 + (bh < NMLP ? SKEW : -2 * SKEW);
            int st = 0, ph = 0;
#pragma unroll 1
            for (int t = NST; t < tend; t++) {
                const uint32_t dst = sb + OFF_RING + st * TILE_BYTES, fb = bar_full + st * 8;
                mbar_wait(bar_empty + st * 8, ph);
                wait_until(t_start, ((t * 16 - lead16) * tile_ns_x16) >> 8);
                if (t == T_W1) {
                    mbar_wait(bar_full + ((T_W1 - 1 - WLATE) % NST) * 8, ((T_W1 - 1 - WLATE) / NST) & 1);
                }
                mbar_expect_tx(fb, TILE_BYTES);
                if (t < T_K1) {
                    tma2d(dst, &tm.wo, rank * 256 + (t - T_WO) * 64, h * DH, fb);
                } else if (t < T_V) {
                    bulk_load_stream(dst, ksrc + (size_t)(t - 8) * TILE_BYTES, TILE_BYTES, fb, pol);
                } else if (t < T_W1) {
                    tma2d_stream(dst, &tm.v, 0, vline0 + (t - T_V) * (TILE_KEYS * 2), fb, pol);
                } else if (t < T_W2) {
                    tma2d(dst, &tm.w1, f0, (t - T_W1) * 256, fb);
                } else {
#pragma unroll
                    for (int i = 0; i < 4; i++) tma2d(dst + i * 4096, &tm.w2, ((t - T_W2) * 4 + i) * 64, f0, fb);
                }
                if (++st == NST) { st = 0; ph ^= 1; }
            }
        }
        if (is_mlp) {
            __syncwarp();
            const int rr = lane & 7, mi = lane >> 3;
            float cs[4][4];
#pragma unroll
            for (int i = 0; i < 4; i++) cs[i][0] = cs[i][1] = cs[i][2] = cs[i][3] = 0.f;
#pragma unroll
            for (int t = 0; t < 2; t++) {
                const uint32_t a = sb + OFF_RING + (T_W1 % NST + t) * TILE_BYTES + ((mi >> 1) * 8 + rr) * 64 + ((mi & 1) ^ (rr >> 1)) * 16;
                mbar_wait(bar_full + (T_W1 % NST + t) * 8, (T_W1 / NST) & 1);
#pragma unroll 4
                for (int k = 0; k < 16; k += 2) {
                    uint32_t w[4][4];
                    ldsm4t(w[0], a + k * 1024); ldsm4t(w[1], (a ^ 32) + k * 1024);
                    ldsm4t(w[2], a + k * 1024 + 1024); ldsm4t(w[3], (a ^ 32) + k * 1024 + 1024);
#pragma unroll
                    for (int i = 0; i < 4; i++) mma_bf16(cs[i], w[i][0], w[i][1], w[i][2], w[i][3], 0x3f803f80u, 0x3f803f80u);
                }
            }
            const int c = lane & 3;
            const float lo = (c & 1) ? cs[0][2] + cs[2][2] : cs[0][0] + cs[2][0], hi = (c & 1) ? cs[1][2] + cs[3][2] : cs[1][0] + cs[3][0];
            sts32(sb + OFF_CS + (c * 8 + (lane >> 2)) * 4, __float_as_uint((c & 2) ? hi : lo));
            asm volatile("bar.arrive 2, 288;" ::: "memory");
        }
        return;
    }

    if (warp == 9) {
        if (is_mlp) {
#pragma unroll
            for (int i = 0; i < 8; i++) g_part[((i * 4 + (lane >> 3)) * NMLP + bh) * 8 + (lane & 7)] = make_uint4(0, 0, 0, 0);
            __threadfence();
        }
        asm volatile("barrier.cluster.wait.aligned;" ::: "memory");
        if (lane == 0) mbar_arrive(bar_o);
        if (is_mlp) {
            mbar_wait(bar_end, 0);
            for (int n = 0;; n++) {
                unsigned v = 0;
                if (lane < 8) asm volatile("ld.relaxed.gpu.global.u32 %0, [%1];" : "=r"(v) : "l"(g_tick + lane * 32) : "memory");
                if (__reduce_add_sync(~0u, v) >= NCTA) break;
                if (n > SPIN_LIMIT) __trap();
            }
            if (lane == 0) mbar_arrive(bar_go);
        }
        return;
    }

    const int g = lane >> 2, c = lane & 3;
    const int rr = lane & 7, mi = lane >> 3;
    const int mb_ = g & 1, j4 = g >> 1;
    const int d0 = warp * 64 + j4 * 16 + c * 2;
    uint32_t qa[16], wf[64];
    {
        if (warp == 6) {
            const uint4 xa0 = __ldg((const uint4*)(x + b * D_MODEL) + lane), xa1 = __ldg((const uint4*)(x + b * D_MODEL) + 32 + lane);
            const uint32_t xa[8] = {xa0.x, xa0.y, xa0.z, xa0.w, xa1.x, xa1.y, xa1.z, xa1.w};
            float s = 0.f;
#pragma unroll
            for (int i = 0; i < 8; i++) s += bf_lo(xa[i]) + bf_hi(xa[i]);
#pragma unroll
            for (int o = 16; o; o >>= 1) s += __shfl_xor_sync(~0u, s, o);
            const float mean = s * (1.0f / D_MODEL);
            float v = 0.f;
#pragma unroll
            for (int i = 0; i < 8; i++) { const float e0 = bf_lo(xa[i]) - mean, e1 = bf_hi(xa[i]) - mean; v += e0 * e0 + e1 * e1; }
#pragma unroll
            for (int o = 16; o; o >>= 1) v += __shfl_xor_sync(~0u, v, o);
            const float mb = rnd_bf(mean);
            const float den = rnd_bf(sqrtf(rnd_bf(rnd_bf(v * (1.0f / D_MODEL)) + 1e-5f)));
#pragma unroll
            for (int i = 0; i < 8; i++) {
                const int k = (i >> 2) * 256 + lane * 8 + (i & 3) * 2;
                sts32(sb + OFF_XN + ((k & ~63) + bpos(k)) * 2,
                      pack_bf(__fdiv_rn(rnd_bf(bf_lo(xa[i]) - mb), den), __fdiv_rn(rnd_bf(bf_hi(xa[i]) - mb), den)));
            }
        }
        asm volatile("barrier.cluster.wait.aligned;" ::: "memory");
        cons_sync();

        float q0[4] = {0.f, 0.f, 0.f, 0.f}, q1[4] = {0.f, 0.f, 0.f, 0.f};
        const uint32_t aoff = ((warp >> 2) * 64 + (mi >> 1) * 8 + rr) * 128 + (((warp & 3) * 2 + (mi & 1)) ^ rr) * 16;
#pragma unroll
        for (int t = 0; t < 4; t++) {
            const uint32_t xaddr = sb + OFF_XN + (t * 2 + (warp >> 2)) * 128 + c * 32;
            const uint4 p0 = lds128(xaddr), p1 = lds128(xaddr + 16);
            const uint32_t base = sb + OFF_RING + (T_WQ + t) * TILE_BYTES + aoff;
            mbar_wait(bar_full + (T_WQ + t) * 8, 0);
            uint32_t a0[4], a1[4], a2[4], a3[4];
            ldsm4t(a0, base); ldsm4t(a1, base + 2048); ldsm4t(a2, base + 4096); ldsm4t(a3, base + 6144);
            mma_bf16(q0, a0[0], a0[1], a0[2], a0[3], p0.x, p0.y);
            mma_bf16(q1, a1[0], a1[1], a1[2], a1[3], p0.z, p0.w);
            mma_bf16(q0, a2[0], a2[1], a2[2], a2[3], p1.x, p1.y);
            mma_bf16(q1, a3[0], a3[1], a3[2], a3[3], p1.z, p1.w);
            __syncwarp();
            if (lane == 0) mbar_arrive(bar_empty + (T_WQ + t) * 8);
        }
        if (c < 2) sts32(sb + OFF_PART + (warp * 16 + c * 8 + g) * 4, __float_as_uint(c ? q0[2] + q1[2] : q0[0] + q1[0]));
        cons_sync();
        if (warp == 0) {
            const uint2 u = lds64(sb + OFF_PART + lane * 8), w = lds64(sb + OFF_PART + 256 + lane * 8);
            const uint32_t qq = pack_bf(__uint_as_float(u.x) + __uint_as_float(w.x), __uint_as_float(u.y) + __uint_as_float(w.y));
            const uint32_t dst = sb + OFF_Q + rank * 128 + lane * 4;
            sts32(dst, qq);
            st_async_b32(mapa(dst, rank ^ 1), qq, mapa(bar_q, rank ^ 1));
            __syncwarp();
            if (lane == 0) mbar_arrive(bar_q);
        }
        mbar_wait(bar_q, 0);
#pragma unroll
        for (int j = 0; j < 16; j++) qa[j] = lds32(sb + OFF_Q + ((j & 8) + ((g + j) & 7)) * 16 + c * 4);
    }

    int st = T_K0, ph = 0;
    float mx = -INFINITY;
    {
        uint32_t koff0 = sb + OFF_RING + (warp * 8 + rr) * 256 + ((rr + mi) & 7) * 16;
        uint32_t koff1 = sb + OFF_RING + (warp * 8 + rr) * 256 + ((rr + mi + 4) & 7) * 16;
        asm volatile("" : "+r"(koff0), "+r"(koff1));
        const bool valid = (c == (g >> 1));
        uint32_t spos = sb + OFF_SP + bpos(warp * 8 + g) * 2;
        auto k_tiles = [&](int n) {
#pragma unroll 1
            for (int i = 0; i < n; i++) {
                const uint32_t base = st * TILE_BYTES;
                mbar_wait(bar_full + st * 8, ph);
                uint32_t k0[4], k1[4], k2[4], k3[4];
                ldsm4(k0, base + koff0); ldsm4(k1, base + koff1);
                ldsm4(k2, base + koff0 + 128); ldsm4(k3, base + koff1 + 128);
                float s0[4] = {0.f, 0.f, 0.f, 0.f}, s1[4] = {0.f, 0.f, 0.f, 0.f};
                mma_bf16(s0, qa[0], qa[2], qa[1], qa[3], k0[0], k0[1]);
                mma_bf16(s1, qa[0], qa[2], qa[1], qa[3], k0[2], k0[3]);
                mma_bf16(s0, qa[4], qa[6], qa[5], qa[7], k1[0], k1[1]);
                mma_bf16(s1, qa[4], qa[6], qa[5], qa[7], k1[2], k1[3]);
                mma_bf16(s0, qa[8], qa[10], qa[9], qa[11], k2[0], k2[1]);
                mma_bf16(s1, qa[8], qa[10], qa[9], qa[11], k2[2], k2[3]);
                mma_bf16(s0, qa[12], qa[14], qa[13], qa[15], k3[0], k3[1]);
                mma_bf16(s1, qa[12], qa[14], qa[13], qa[15], k3[2], k3[3]);
                __syncwarp();
                if (lane == 0) mbar_arrive(bar_empty + st * 8);
                const float raw = (g & 1) ? s0[1] + s1[3] : s0[0] + s1[2];
                const uint32_t sc = pack_bf(rnd_bf(raw) * 0.08838834764831845f, 0.f);
                if (valid) { sts16(spos, (uint16_t)sc); mx = fmaxf(mx, bf_lo(sc)); }
                spos += TILE_KEYS * 2;
                if (++st == NST) { st = 0; ph ^= 1; }
            }
        };
        k_tiles(KPRE);
        {
            static_assert(T_WO == NST, "wo tiles sit in slots 0..3, second pass");
            const int s = warp >> 1;
            const int row = (mi >> 1) * 4 + (rr >> 1) + (rr & 1) * 8;
            const uint32_t base = sb + OFF_RING + s * TILE_BYTES + row * 128;
            const uint32_t c0 = (((mi & 1) * 2 + (warp & 1)) ^ (row & 7)) * 16, c1 = c0 ^ 64;
            mbar_wait(bar_full + s * 8, 1);
#pragma unroll
            for (int t = 0; t < 8; t++) {
                ldsm4t(*(uint32_t(*)[4])(wf + 8 * t), base + t * 2048 + c0);
                ldsm4t(*(uint32_t(*)[4])(wf + 8 * t + 4), base + t * 2048 + c1);
            }
            __syncwarp();
            if (lane < 4) mbar_arrive(bar_empty + lane * 8);
            st = 4;
        }
        k_tiles(NTILE - KPRE);
    }
    {
#pragma unroll
        for (int o = 16; o; o >>= 1) mx = fmaxf(mx, __shfl_xor_sync(~0u, mx, o));
        if (lane == 0) sts32(sb + OFF_RED + warp * 4, __float_as_uint(mx));
        cons_sync();
        const uint4 m0 = lds128(sb + OFF_RED), m1 = lds128(sb + OFF_RED + 16);
        const float mloc = fmaxf(fmaxf(fmaxf(__uint_as_float(m0.x), __uint_as_float(m0.y)), fmaxf(__uint_as_float(m0.z), __uint_as_float(m0.w))),
                                 fmaxf(fmaxf(__uint_as_float(m1.x), __uint_as_float(m1.y)), fmaxf(__uint_as_float(m1.z), __uint_as_float(m1.w))));
        const uint4 s0 = lds128(sb + OFF_SP + tid * 16), s1 = lds128(sb + OFF_SP + 4096 + tid * 16);
        const uint32_t sv[8] = {s0.x, s0.y, s0.z, s0.w, s1.x, s1.y, s1.z, s1.w};
        constexpr float LOG2E = 1.4426950408889634f;
        float l = 0.f;
#pragma unroll
        for (int i = 0; i < 8; i++) l += exp2f((bf_lo(sv[i]) - mloc) * LOG2E) + exp2f((bf_hi(sv[i]) - mloc) * LOG2E);
#pragma unroll
        for (int o = 16; o; o >>= 1) l += __shfl_xor_sync(~0u, l, o);
        if (lane == 0) sts32(sb + OFF_RED + 32 + warp * 4, __float_as_uint(l));
        cons_sync();
        const uint4 l0 = lds128(sb + OFF_RED + 32), l1 = lds128(sb + OFF_RED + 48);
        const float lloc = ((__uint_as_float(l0.x) + __uint_as_float(l0.y)) + (__uint_as_float(l0.z) + __uint_as_float(l0.w))) +
                           ((__uint_as_float(l1.x) + __uint_as_float(l1.y)) + (__uint_as_float(l1.z) + __uint_as_float(l1.w)));
        if (tid == 0) st_async_v2(mapa(sb + OFF_ML, rank ^ 1), __float_as_uint(mloc), __float_as_uint(lloc), mapa(bar_ml, rank ^ 1));
        mbar_wait(bar_ml, 0);
        const uint2 pml = lds64(sb + OFF_ML);
        const float mp = __uint_as_float(pml.x), lp = __uint_as_float(pml.y);
        const float M = fmaxf(mloc, mp);
        const float m_a = rank ? mp : mloc, l_a = rank ? lp : lloc, m_b = rank ? mloc : mp, l_b = rank ? lloc : lp;
        const float L = l_a * exp2f((m_a - M) * LOG2E) + l_b * exp2f((m_b - M) * LOG2E);
        const float inv = 1.0f / L;
        uint32_t pv[8];
#pragma unroll
        for (int i = 0; i < 8; i++)
            pv[i] = pack_bf(exp2f((bf_lo(sv[i]) - M) * LOG2E) * inv, exp2f((bf_hi(sv[i]) - M) * LOG2E) * inv);
        sts128(sb + OFF_SP + tid * 16, make_uint4(pv[0], pv[1], pv[2], pv[3]));
        sts128(sb + OFF_SP + 4096 + tid * 16, make_uint4(pv[4], pv[5], pv[6], pv[7]));
        cons_sync();
    }
    unsigned long long* acc1_dst = g_acc1 + b * D_MODEL + rank * 256 + warp * 32 + c * 8 + g;
    uint32_t o_dst = sb + OFF_O + (rank * 2 + (c & 1)) * O_STRIDE + (warp * 8 + g) * 4, o_bar = bar_o;
    if (c & 2) { o_dst = mapa(o_dst, rank ^ 1); o_bar = mapa(bar_o, rank ^ 1); }
    uint32_t o_src = sb + OFF_O + (rr & 3) * O_STRIDE + mi * 16;
    unsigned* tick_dst = g_tick + (bh & 7) * 32;
    asm volatile("" : "+l"(acc1_dst), "+l"(tick_dst), "+r"(o_dst), "+r"(o_bar), "+r"(o_src));
    const bool is_fin = bh < NFIN;
    const unsigned long long* p1 = g_acc1 + mb_ * D_MODEL + warp * 64 + j4 * 8 + c * 2;
    uint4* part_dst = g_part + ((warp * 4 + c) * NMLP + bh) * 8 + g;
    const uint4* inbox = g_part + bh * (NMLP * 8) + tid;
    const uint4* inbox2 = tid < (NMLP - 32) * 8 ? inbox + 256 : inbox;
    const uint4* inbox_pf = g_part + (bh * NMLP + tid) * 8;
    int do_pf = is_fin && tid < NMLP;
    float wsel = tid < (NMLP - 32) * 8 ? 1.0f : 0.0f;
    __nv_bfloat16* out_dst = out + ((lane >> 3) & 1) * D_MODEL + bh * 16 + (lane >> 4) * 8 + (lane & 7);
    asm volatile("" : "+l"(p1), "+l"(part_dst), "+l"(inbox), "+l"(inbox2), "+l"(inbox_pf), "+r"(do_pf), "+f"(wsel), "+l"(out_dst));
    uint32_t xv[2] = {lds32(sb + OFF_X + (mb_ * D_MODEL + d0) * 2), lds32(sb + OFF_X + (mb_ * D_MODEL + d0 + 8) * 2)};
    float b1v = bf16_at(sb + OFF_X + 3072 + lane * 2);
    float b2v = bf16_at(sb + OFF_X + 2048 + ((bh & 31) * 16 + (lane >> 4) * 8 + (lane & 7)) * 2);
    uint32_t a_part = sb + OFF_PART + warp * 256 + ((c >> 1) * 32 + (c & 1) * 16 + g) * 4;
    uint32_t a_stat = sb + OFF_STAT + (mb_ * 16 + (c & 1) * 8 + warp) * 4;
    uint32_t a_keep = sb + OFF_RED + mb_ * 32 + c * 4;
    uint32_t a_sum = sb + OFF_PART + (warp * 32 + lane) * 4, a_cs = sb + OFF_CS + lane * 4;
    uint32_t a_hid = sb + OFF_HID + warp * 80 + lane * 2, a_hidb = sb + OFF_HID + (rr & 1) * 80 + mi * 16;
    uint32_t a_fin = sb + OFF_PART + warp * 256 + lane * 4;
    uint32_t a_hfin = sb + OFF_RED + ((lane >> 3) & 1) * 32 + ((lane >> 4) * 8 + (lane & 7)) * 2;
    int keep_h = warp * 4 + j4 == bh;
    asm volatile("" : "+r"(a_part), "+r"(a_stat), "+r"(a_keep), "+r"(a_sum), "+r"(a_cs), "+r"(a_hid), "+r"(a_hidb), "+r"(a_fin), "+r"(a_hfin),
                 "+r"(keep_h), "+f"(b1v), "+f"(b2v));
    static_assert(T_W1 % NST + 3 < NST, "w1/w2 occupy four consecutive slots with the same parity");
    constexpr int W_PAR = (T_W1 / NST) & 1;
    uint32_t w1_bar = bar_full + (T_W1 % NST + (warp >> 2)) * 8;
    uint32_t w1_a = sb + OFF_RING + (T_W1 % NST + (warp >> 2)) * TILE_BYTES + ((warp & 3) * 64 + (mi >> 1) * 8 + rr) * 64 + ((mi & 1) ^ (rr >> 1)) * 16;
    uint32_t w2_a = sb + OFF_RING + (T_W2 % NST + (warp >> 2)) * TILE_BYTES + (warp & 3) * 4096 + ((mi >> 1) * 8 + rr) * 128 + ((mi & 1) ^ rr) * 16;
    asm volatile("" : "+r"(w1_bar), "+r"(w1_a), "+r"(w2_a));
    {
        const int hh = warp >> 2, ch = 2 * (warp & 3);
        const int line = 2 * (8 * (mi >> 1) + rr) + hh;
        uint32_t voff = sb + OFF_RING + line * 128 + (((ch ^ (mi & 1) ^ (rr >> 2)) ^ (line & 7)) * 16);
        uint32_t pmask = ((c >> 1) == (g & 1)) ? 0xffffffffu : 0u;
        asm volatile("" : "+r"(voff), "+r"(pmask));
        uint32_t paddr = sb + OFF_SP + c * 32;
        float o0[4] = {0.f, 0.f, 0.f, 0.f}, o1[4] = {0.f, 0.f, 0.f, 0.f};
#pragma unroll 1
        for (int i = 0; i < NTILE; i++) {
            const uint32_t base = voff + st * TILE_BYTES;
            uint4 p0 = lds128(paddr), p1 = lds128(paddr + 16);
            p0.x &= pmask; p0.y &= pmask; p0.z &= pmask; p0.w &= pmask;
            p1.x &= pmask; p1.y &= pmask; p1.z &= pmask; p1.w &= pmask;
            asm volatile("" : "+r"(p0.x), "+r"(p0.y), "+r"(p0.z), "+r"(p0.w), "+r"(p1.x), "+r"(p1.y), "+r"(p1.z), "+r"(p1.w));
            mbar_wait(bar_full + st * 8, ph);
            uint32_t a0[4], a1[4], a2[4], a3[4];
            ldsm4t(a0, base); ldsm4t(a1, base + 4096); ldsm4t(a2, base + 8192); ldsm4t(a3, base + 12288);
            if (i == NTILE - 1 && tid == 0) {
                asm volatile("red.relaxed.gpu.global.add.u32 [%0], 1;" ::"l"(tick_dst) : "memory");
                mbar_arrive(bar_end);
            }
            mma_bf16(o0, a0[0], a0[1], a0[2], a0[3], p0.x, p0.y);
            mma_bf16(o1, a1[0], a1[1], a1[2], a1[3], p0.z, p0.w);
            mma_bf16(o0, a2[0], a2[1], a2[2], a2[3], p1.x, p1.y);
            mma_bf16(o1, a3[0], a3[1], a3[2], a3[3], p1.z, p1.w);
            __syncwarp();
            if (lane == 0) mbar_arrive(bar_empty + st * 8);
            paddr += TILE_KEYS * 2;
            if (++st == NST) { st = 0; ph ^= 1; }
        }
        const float v0 = (o0[0] + o1[0]) + (o0[3] + o1[3]);
        const float v1 = (o0[1] + o1[1]) + (o0[2] + o1[2]);
        const uint32_t hi = pack_bf(v0, v1);
        const uint32_t val = (c & 1) ? pack_bf(v0 - bf_lo(hi), v1 - bf_hi(hi)) : hi;
        if (c & 2) st_async_b32(o_dst, val, o_bar);
        else sts32(o_dst, val);
        __syncwarp();
        if (lane == 0) mbar_arrive(bar_o);
        mbar_wait(bar_o, 0);
    }
    {
        float d00[4] = {0.f, 0.f, 0.f, 0.f}, d01[4] = {0.f, 0.f, 0.f, 0.f}, d10[4] = {0.f, 0.f, 0.f, 0.f}, d11[4] = {0.f, 0.f, 0.f, 0.f};
        uint32_t ob[4][4];
#pragma unroll
        for (int t = 0; t < 4; t++) ldsm4(ob[t], o_src + t * 64);
#pragma unroll
        for (int t = 0; t < 4; t++) {
            mma_bf16(d00, wf[16 * t], wf[16 * t + 1], wf[16 * t + 2], wf[16 * t + 3], ob[t][0], ob[t][1]);
            mma_bf16(d10, wf[16 * t + 4], wf[16 * t + 5], wf[16 * t + 6], wf[16 * t + 7], ob[t][0], ob[t][1]);
            mma_bf16(d01, wf[16 * t + 8], wf[16 * t + 9], wf[16 * t + 10], wf[16 * t + 11], ob[t][2], ob[t][3]);
            mma_bf16(d11, wf[16 * t + 12], wf[16 * t + 13], wf[16 * t + 14], wf[16 * t + 15], ob[t][2], ob[t][3]);
        }
        const float e0 = (d00[0] + d01[0]) + (d00[1] + d01[1]), e1 = (d00[2] + d01[2]) + (d00[3] + d01[3]);
        const float e2 = (d10[0] + d11[0]) + (d10[1] + d11[1]), e3 = (d10[2] + d11[2]) + (d10[3] + d11[3]);
        const float ea = (c & 2) ? e2 : e0, eb = (c & 2) ? e3 : e1;
        const float e = ((c & 1) ? eb : ea) + __shfl_xor_sync(~0u, (c & 1) ? ea : eb, 1);
        red_add64(acc1_dst, fx_encode(e));
    }
    if (!is_mlp) return;

    {
        if (do_pf) asm volatile("prefetch.global.L2 [%0];" ::"l"(inbox_pf));
        uint32_t* a1 = wf;
        uint32_t* a2 = wf + 32;
        auto load_w1 = [&]() {
#pragma unroll
            for (int k = 0; k < 4; k++) {
                ldsm4t(*(uint32_t(*)[4])(a1 + 8 * k), w1_a + k * 1024);
                ldsm4t(*(uint32_t(*)[4])(a1 + 8 * k + 4), (w1_a ^ 32) + k * 1024);
            }
        };
        auto load_w2 = [&]() {
#pragma unroll
            for (int u = 0; u < 2; u++)
#pragma unroll
                for (int T = 0; T < 4; T++) ldsm4t(*(uint32_t(*)[4])(a2 + 16 * u + 4 * T), (w2_a ^ (T * 32)) + u * 2048);
        };
        uint32_t hb0, hb1;
        int stage = 0;
        {
            uint4 ua = make_uint4(0, 0, 0, 0), ub = ua;
            int n = 0, polled = 0;
#pragma unroll 1
            do {
                if (!polled && __all_sync(~0u, mbar_test(bar_go, 0))) {
                    ld_relaxed2x64(ua, p1); ld_relaxed2x64(ub, p1 + 32);
                    polled = 1;
                }
                if (stage < 2 && __all_sync(~0u, mbar_test(w1_bar + stage * 16, W_PAR))) {
                    if (stage == 0) load_w1(); else load_w2();
                    stage++;
                }
                if (++n > SPIN_LIMIT * 16) __trap();
            } while (stage < 1 || !polled);
            if (stage < 2 && __all_sync(~0u, mbar_test(w1_bar + 16, W_PAR))) { load_w2(); stage = 2; }
            n = 0;
            while (!all_complete(ua, ub)) {
                ld_relaxed2x64(ua, p1); ld_relaxed2x64(ub, p1 + 32);
                if (++n > SPIN_LIMIT) __trap();
            }
            const uint32_t at0 = pack_bf(fx_decode(ua.x, ua.y), fx_decode(ua.z, ua.w)), at1 = pack_bf(fx_decode(ub.x, ub.y), fx_decode(ub.z, ub.w));
            hb0 = pack_bf(bf_lo(xv[0]) + bf_lo(at0), bf_hi(xv[0]) + bf_hi(at0));
            hb1 = pack_bf(bf_lo(xv[1]) + bf_lo(at1), bf_hi(xv[1]) + bf_hi(at1));
        }
        gemv1_partial(a1, hb0, hb1, j4, c, a_part);
        {
            const float h0 = bf_lo(hb0), h1 = bf_hi(hb0), h2 = bf_lo(hb1), h3 = bf_hi(hb1);
            const float s1 = (h0 + h1) + (h2 + h3);
            const float s2 = (h0 * h0 + h1 * h1) + (h2 * h2 + h3 * h3);
            float t = ((c & 1) ? s2 : s1) + __shfl_xor_sync(~0u, (c & 1) ? s1 : s2, 1);
            t += __shfl_xor_sync(~0u, t, 2);
            t += __shfl_xor_sync(~0u, t, 8);
            t += __shfl_xor_sync(~0u, t, 16);
            if ((lane & 0x1a) == 0) sts32(a_stat, __float_as_uint(t));
        }
        if (keep_h) {
            sts32(a_keep, hb0);
            sts32(a_keep + 16, hb1);
        }
        asm volatile("bar.sync 2, 288;" ::: "memory");
        if (warp < 2) {
            const uint4 q0 = lds128(sb + OFF_STAT + warp * 64), q1 = lds128(sb + OFF_STAT + warp * 64 + 16);
            const uint4 q2 = lds128(sb + OFF_STAT + warp * 64 + 32), q3 = lds128(sb + OFF_STAT + warp * 64 + 48);
            const float sacc = sum8(a_sum);
            const float cs = __uint_as_float(lds32(a_cs));
            const float mean = (((__uint_as_float(q0.x) + __uint_as_float(q0.y)) + (__uint_as_float(q0.z) + __uint_as_float(q0.w))) +
                                ((__uint_as_float(q1.x) + __uint_as_float(q1.y)) + (__uint_as_float(q1.z) + __uint_as_float(q1.w)))) * (1.0f / D_MODEL);
            const float msq = (((__uint_as_float(q2.x) + __uint_as_float(q2.y)) + (__uint_as_float(q2.z) + __uint_as_float(q2.w))) +
                               ((__uint_as_float(q3.x) + __uint_as_float(q3.y)) + (__uint_as_float(q3.z) + __uint_as_float(q3.w)))) * (1.0f / D_MODEL);
            const float var = fmaxf(msq - mean * mean, 0.f);
            float sq, iden;
            asm("sqrt.approx.ftz.f32 %0, %1;" : "=f"(sq) : "f"(rnd_bf(rnd_bf(var) + 1e-5f)));
            asm("rcp.approx.ftz.f32 %0, %1;" : "=f"(iden) : "f"(rnd_bf(sq)));
            const float z = fmaxf(rnd_bf(rnd_bf((sacc - rnd_bf(mean) * cs) * iden) + b1v), 0.f);
            sts16(a_hid, (uint16_t)pack_bf(z * z, 0.f));
        }
        if (stage < 2) { mbar_wait(w1_bar + 16, W_PAR); load_w2(); }
        cons_sync();
        uint32_t hb[4];
        ldsm4(hb, a_hidb);
        const float hfin = bf16_at(a_hfin);
        float y[4][4];
#pragma unroll
        for (int T = 0; T < 4; T++) {
            y[T][0] = y[T][1] = y[T][2] = y[T][3] = 0.f;
            mma_bf16(y[T], a2[4 * T], a2[4 * T + 1], a2[4 * T + 2], a2[4 * T + 3], hb[0], hb[1]);
        }
#pragma unroll
        for (int T = 0; T < 4; T++)
            mma_bf16(y[T], a2[16 + 4 * T], a2[16 + 4 * T + 1], a2[16 + 4 * T + 2], a2[16 + 4 * T + 3], hb[2], hb[3]);
        {
            const bool up2 = c & 2, up1 = c & 1;
            uint32_t e[4];
#pragma unroll
            for (int i = 0; i < 4; i++) e[i] = __float_as_uint(up2 ? (up1 ? y[3][i] : y[2][i]) : (up1 ? y[1][i] : y[0][i])) | 1u;
            asm volatile("st.relaxed.gpu.global.v4.u32 [%0], {%1,%2,%3,%4};" ::"l"(part_dst), "r"(e[0]), "r"(e[1]), "r"(e[2]), "r"(e[3]) : "memory");
        }
        if (!is_fin) return;
        {
            uint4 u, w;
            int n = 0;
            spin_cycles(DELAY2);
            do {
                ld_relaxed128(u, inbox); ld_relaxed128(w, inbox2);
                if (++n > SPIN_LIMIT) __trap();
            } while (!all_marked(u, w));
            const float v0 = fmaf(__uint_as_float(w.x), wsel, __uint_as_float(u.x)), v1 = fmaf(__uint_as_float(w.y), wsel, __uint_as_float(u.y));
            const float v2 = fmaf(__uint_as_float(w.z), wsel, __uint_as_float(u.z)), v3 = fmaf(__uint_as_float(w.w), wsel, __uint_as_float(u.w));
            const bool up16 = lane & 16, up8 = lane & 8;
            const float r0 = (up16 ? v2 : v0) + __shfl_xor_sync(~0u, up16 ? v0 : v2, 16);
            const float r1 = (up16 ? v3 : v1) + __shfl_xor_sync(~0u, up16 ? v1 : v3, 16);
            const float r = (up8 ? r1 : r0) + __shfl_xor_sync(~0u, up8 ? r0 : r1, 8);
            sts32(a_fin, __float_as_uint(r));
        }
        cons_sync();
        if (warp == 0) {
            const float y2 = sum8(a_sum);
            *out_dst = __ushort_as_bfloat16((unsigned short)pack_bf(hfin + rnd_bf(rnd_bf(y2) + b2v), 0.f));
        }
        if (bh == 0) {
            *(ulonglong2*)(g_acc1 + tid * 4) = make_ulonglong2(0, 0);
            *(ulonglong2*)(g_acc1 + tid * 4 + 2) = make_ulonglong2(0, 0);
            if (tid < 8) g_tick[tid * 32] = 0;
        }
    }
}

typedef CUresult (*EncodeFn)(CUtensorMap*, CUtensorMapDataType, cuuint32_t, void*, const cuuint64_t*, const cuuint64_t*,
                             const cuuint32_t*, const cuuint32_t*, CUtensorMapInterleave, CUtensorMapSwizzle,
                             CUtensorMapL2promotion, CUtensorMapFloatOOBfill);

void make_map(EncodeFn enc, CUtensorMap* tm, void* ptr, uint64_t cols, uint64_t rows, uint32_t box_cols, uint32_t box_rows,
              CUtensorMapSwizzle swz) {
    const cuuint64_t dims[2] = {cols, rows};
    const cuuint64_t strides[1] = {cols * 2};
    const cuuint32_t box[2] = {box_cols, box_rows};
    const cuuint32_t es[2] = {1, 1};
    enc(tm, CU_TENSOR_MAP_DATA_TYPE_BFLOAT16, 2, ptr, dims, strides, box, es, CU_TENSOR_MAP_INTERLEAVE_NONE, swz,
        CU_TENSOR_MAP_L2_PROMOTION_NONE, CU_TENSOR_MAP_FLOAT_OOB_FILL_NONE);
}

}

extern "C" void kernel_launch(void* const* d_in, const int* in_sizes, int n_in, void* d_out, int out_size) {
    (void)in_sizes; (void)n_in; (void)out_size;
    static EncodeFn enc = nullptr;
    static Scratch* scr = nullptr;
    static uint32_t tile_ns_x16 = 0;
    if (!enc) {
        void* fn = nullptr;
        cudaDriverEntryPointQueryResult qr;
        cudaGetDriverEntryPoint("cuTensorMapEncodeTiled", &fn, cudaEnableDefault, &qr);
        enc = (EncodeFn)fn;
        cudaGetSymbolAddress((void**)&scr, g_scratch);
        int dev = 0, mem_khz = 0, bus_bits = 0;
        cudaGetDevice(&dev);
        cudaDeviceGetAttribute(&mem_khz, cudaDevAttrMemoryClockRate, dev);
        cudaDeviceGetAttribute(&bus_bits, cudaDevAttrGlobalMemoryBusWidth, dev);
        const double bytes_per_ns = 2.0 * mem_khz * 1e-6 * (bus_bits / 8) * (PACE * 1e-3);
        if (bytes_per_ns > 0) tile_ns_x16 = (uint32_t)(16.0 * NCTA * TILE_BYTES / bytes_per_ns);
        cudaFuncSetAttribute(decode_block_kernel, cudaFuncAttributeMaxDynamicSharedMemorySize, SMEM_BYTES);
    }
    Maps tm;
    make_map(enc, &tm.v, d_in[2], 64, (uint64_t)2 * NHEAD * SK * 2, 64, TILE_KEYS * 2, CU_TENSOR_MAP_SWIZZLE_128B);
    make_map(enc, &tm.wq, d_in[3], QCOLS, D_MODEL, 64, 128, CU_TENSOR_MAP_SWIZZLE_128B);
    make_map(enc, &tm.wo, d_in[4], D_MODEL, QCOLS, 64, 128, CU_TENSOR_MAP_SWIZZLE_128B);
    make_map(enc, &tm.w1, d_in[6], FF, D_MODEL, 32, 256, CU_TENSOR_MAP_SWIZZLE_64B);
    make_map(enc, &tm.w2, d_in[8], D_MODEL, FF, 64, 32, CU_TENSOR_MAP_SWIZZLE_128B);
    decode_block_kernel<<<NCTA, NTHREADS, SMEM_BYTES>>>(
        tm, (const __nv_bfloat16*)d_in[0], (const __nv_bfloat16*)d_in[1], (const __nv_bfloat16*)d_in[7],
        (const __nv_bfloat16*)d_in[9], (__nv_bfloat16*)d_out, scr, tile_ns_x16);
}
```

```cpp
#include <cuda_runtime.h>
#include <cuda_bf16.h>
#include <cuda.h>
#include <stdint.h>

namespace {

constexpr int D_MODEL = 512;
constexpr int NHEAD = 32;
constexpr int SK = 8192;
constexpr int DH = 128;
constexpr int FF = 1376;
constexpr int QCOLS = NHEAD * DH;

constexpr int NCTA = 128;
constexpr int KEYS_PER_CTA = SK / 2;
constexpr int TILE_KEYS = 64;
constexpr int TILE_BYTES = TILE_KEYS * DH * 2;
constexpr int NTILE = KEYS_PER_CTA / TILE_KEYS;
constexpr int NST = 12;
constexpr int NINIT = 5;
constexpr int WLATE = 1;
constexpr int LEAD = 7;
constexpr int PACE = 958;
constexpr int SKEW = 8;
constexpr int DELAY2 = 300;
constexpr int NCONS = 256;
constexpr int NTHREADS = NCONS + 64;
constexpr int NMLP = FF / 32;
constexpr int KPRE = NST - 4;
constexpr int T_WQ = 0, T_K0 = 4, T_WO = T_K0 + KPRE, T_K1 = T_WO + 4, T_V = T_K1 + NTILE - KPRE, T_W1 = T_V + NTILE,
              T_W2 = T_W1 + 2, T_END = T_W2 + 2;

constexpr int OFF_RING = 0;
constexpr int OFF_SP = OFF_RING + NST * TILE_BYTES;
constexpr int OFF_PART = OFF_SP + KEYS_PER_CTA * 2;
constexpr int OFF_CS = OFF_PART + 8 * 64 * 4;
constexpr int OFF_XN = OFF_CS + 32 * 4;
constexpr int OFF_X = OFF_XN + 1024;
constexpr int O_STRIDE = 272;
constexpr int OFF_O = OFF_X + 2048 + 1024 + 64;
constexpr int OFF_Q = OFF_O + 4 * O_STRIDE;
constexpr int OFF_RED = OFF_Q + 256;
constexpr int OFF_STAT = OFF_RED + 64;
constexpr int OFF_HID = OFF_STAT + 128;
constexpr int OFF_ML = OFF_HID + 160;
constexpr int OFF_BAR = OFF_ML + 16;
constexpr int SMEM_USED = OFF_BAR + (2 * NST + 5) * 8;
constexpr int SMEM_BYTES = SMEM_USED + 1024;

constexpr float FX_SCALE = 1073741824.0f;
constexpr float FX_INV = 1.0f / 1073741824.0f;

constexpr int NFIN = 32;
struct Scratch {
    unsigned long long acc1[2 * D_MODEL];
    unsigned int tick[8 * 32];
    uint4 part[NFIN * NMLP * 8];
};
__device__ __align__(1024) Scratch g_scratch;

__device__ __forceinline__ void mbar_init(uint32_t bar, uint32_t cnt) {
    asm volatile("mbarrier.init.shared::cta.b64 [%0], %1;" ::"r"(bar), "r"(cnt) : "memory");
}
__device__ __forceinline__ void mbar_expect_tx(uint32_t bar, uint32_t bytes) {
    asm volatile("mbarrier.arrive.expect_tx.shared::cta.b64 _, [%0], %1;" ::"r"(bar), "r"(bytes) : "memory");
}
__device__ __forceinline__ void mbar_arrive(uint32_t bar) {
    asm volatile("mbarrier.arrive.shared::cta.b64 _, [%0];" ::"r"(bar) : "memory");
}
__device__ __forceinline__ bool mbar_test(uint32_t bar, uint32_t parity) {
    uint32_t ok;
    asm volatile("{\n.reg .pred p;\nmbarrier.test_wait.parity.shared::cta.b64 p, [%1], %2;\nselp.u32 %0, 1, 0, p;\n}"
                 : "=r"(ok) : "r"(bar), "r"(parity) : "memory");
    return ok;
}
__device__ __forceinline__ bool mbar_try(uint32_t bar, uint32_t parity) {
    uint32_t ok;
    asm volatile("{\n.reg .pred p;\nmbarrier.try_wait.parity.shared::cta.b64 p, [%1], %2;\nselp.u32 %0, 1, 0, p;\n}"
                 : "=r"(ok) : "r"(bar), "r"(parity) : "memory");
    return ok;
}
constexpr int SPIN_LIMIT = 1 << 20;
__device__ __forceinline__ void mbar_wait(uint32_t bar, uint32_t parity) {
    int n = 0;
    while (!mbar_try(bar, parity)) { if (++n > SPIN_LIMIT) __trap(); }
}
__device__ __forceinline__ void bulk_load(uint32_t dst, const void* src, uint32_t bytes, uint32_t bar) {
    asm volatile("cp.async.bulk.shared::cluster.global.mbarrier::complete_tx::bytes [%0], [%1], %2, [%3];"
                 ::"r"(dst), "l"(src), "r"(bytes), "r"(bar) : "memory");
}
__device__ __forceinline__ void tma2d(uint32_t dst, const CUtensorMap* tm, int c0, int c1, uint32_t bar) {
    asm volatile("cp.async.bulk.tensor.2d.shared::cluster.global.mbarrier::complete_tx::bytes [%0], [%1, {%3, %4}], [%2];"
                 ::"r"(dst), "l"(tm), "r"(bar), "r"(c0), "r"(c1) : "memory");
}
__device__ __forceinline__ void bulk_load_stream(uint32_t dst, const void* src, uint32_t bytes, uint32_t bar, uint64_t pol) {
    asm volatile("cp.async.bulk.shared::cluster.global.mbarrier::complete_tx::bytes.L2::cache_hint [%0], [%1], %2, [%3], %4;"
                 ::"r"(dst), "l"(src), "r"(bytes), "r"(bar), "l"(pol) : "memory");
}
__device__ __forceinline__ void tma2d_stream(uint32_t dst, const CUtensorMap* tm, int c0, int c1, uint32_t bar, uint64_t pol) {
    asm volatile("cp.async.bulk.tensor.2d.shared::cluster.global.mbarrier::complete_tx::bytes.L2::cache_hint [%0], [%1, {%3, %4}], [%2], %5;"
                 ::"r"(dst), "l"(tm), "r"(bar), "r"(c0), "r"(c1), "l"(pol) : "memory");
}
__device__ __forceinline__ bool elect_one() {
    uint32_t p;
    asm volatile("{\n.reg .pred p;\nelect.sync _|p, 0xffffffff;\nselp.u32 %0, 1, 0, p;\n}" : "=r"(p));
    return p;
}
__device__ __forceinline__ void cons_sync() { asm volatile("bar.sync 1, 256;" ::: "memory"); }

__device__ __forceinline__ uint32_t mapa(uint32_t addr, uint32_t rank) {
    uint32_t r;
    asm("mapa.shared::cluster.u32 %0, %1, %2;" : "=r"(r) : "r"(addr), "r"(rank));
    return r;
}
__device__ __forceinline__ void st_async_b32(uint32_t addr, uint32_t v, uint32_t bar) {
    asm volatile("st.async.weak.shared::cluster.mbarrier::complete_tx::bytes.b32 [%0], %1, [%2];" ::"r"(addr), "r"(v), "r"(bar) : "memory");
}
__device__ __forceinline__ void st_async_v2(uint32_t addr, uint32_t v0, uint32_t v1, uint32_t bar) {
    asm volatile("st.async.weak.shared::cluster.mbarrier::complete_tx::bytes.v2.b32 [%0], {%1, %2}, [%3];" ::"r"(addr), "r"(v0), "r"(v1), "r"(bar) : "memory");
}

__device__ __forceinline__ void mma_bf16(float (&d)[4], uint32_t a0, uint32_t a1, uint32_t a2, uint32_t a3, uint32_t b0, uint32_t b1) {
    asm volatile("mma.sync.aligned.m16n8k16.row.col.f32.bf16.bf16.f32 {%0,%1,%2,%3}, {%4,%5,%6,%7}, {%8,%9}, {%0,%1,%2,%3};"
                 : "+f"(d[0]), "+f"(d[1]), "+f"(d[2]), "+f"(d[3])
                 : "r"(a0), "r"(a1), "r"(a2), "r"(a3), "r"(b0), "r"(b1));
}
__device__ __forceinline__ void ldsm4(uint32_t (&r)[4], uint32_t addr) {
    asm volatile("ldmatrix.sync.aligned.m8n8.x4.shared.b16 {%0,%1,%2,%3}, [%4];"
                 : "=r"(r[0]), "=r"(r[1]), "=r"(r[2]), "=r"(r[3]) : "r"(addr) : "memory");
}
__device__ __forceinline__ void ldsm4t(uint32_t (&r)[4], uint32_t addr) {
    asm volatile("ldmatrix.sync.aligned.m8n8.x4.trans.shared.b16 {%0,%1,%2,%3}, [%4];"
                 : "=r"(r[0]), "=r"(r[1]), "=r"(r[2]), "=r"(r[3]) : "r"(addr) : "memory");
}
__device__ __forceinline__ uint4 lds128(uint32_t a) {
    uint4 v;
    asm volatile("ld.shared.v4.u32 {%0,%1,%2,%3}, [%4];" : "=r"(v.x), "=r"(v.y), "=r"(v.z), "=r"(v.w) : "r"(a) : "memory");
    return v;
}
__device__ __forceinline__ uint2 lds64(uint32_t a) {
    uint2 v;
    asm volatile("ld.shared.v2.u32 {%0,%1}, [%2];" : "=r"(v.x), "=r"(v.y) : "r"(a) : "memory");
    return v;
}
__device__ __forceinline__ uint32_t lds32(uint32_t a) {
    uint32_t v;
    asm volatile("ld.shared.u32 %0, [%1];" : "=r"(v) : "r"(a) : "memory");
    return v;
}
__device__ __forceinline__ void sts128(uint32_t a, uint4 v) {
    asm volatile("st.shared.v4.u32 [%0], {%1,%2,%3,%4};" ::"r"(a), "r"(v.x), "r"(v.y), "r"(v.z), "r"(v.w) : "memory");
}
__device__ __forceinline__ void sts32(uint32_t a, uint32_t v) {
    asm volatile("st.shared.u32 [%0], %1;" ::"r"(a), "r"(v) : "memory");
}
__device__ __forceinline__ void sts16(uint32_t a, uint16_t v) {
    asm volatile("st.shared.u16 [%0], %1;" ::"r"(a), "h"(v) : "memory");
}
__device__ __forceinline__ float bf_lo(uint32_t v) { return __uint_as_float(v << 16); }
__device__ __forceinline__ float bf_hi(uint32_t v) { return __uint_as_float(v & 0xffff0000u); }
__device__ __forceinline__ uint32_t pack_bf(float lo, float hi) {
    uint32_t r;
    asm("cvt.rn.bf16x2.f32 %0, %1, %2;" : "=r"(r) : "f"(hi), "f"(lo));
    return r;
}
__device__ __forceinline__ float rnd_bf(float v) { return bf_lo(pack_bf(v, 0.f)); }

__device__ __forceinline__ unsigned long long fx_encode(float v) {
    return ((unsigned long long)__float2ll_rn(v * FX_SCALE) << 8) + 1ull;
}
__device__ __forceinline__ float fx_decode(uint32_t lo, uint32_t hi) {
    return fmaf(__int2float_rn((int)hi), 1.0f / 64.0f, __uint2float_rn(lo & 0xffffff00u) * (FX_INV / 256.0f));
}
__device__ __forceinline__ uint32_t gtime32() {
    uint32_t t;
    asm volatile("mov.u32 %0, %%globaltimer_lo;" : "=r"(t));
    return t;
}
__device__ __forceinline__ void wait_until(uint32_t t0, uint32_t ns) {
    for (int n = 0; gtime32() - t0 < ns && n < SPIN_LIMIT; n++) {}
}
__device__ __forceinline__ void spin_cycles(uint32_t n) {
    uint32_t t0, t;
    asm volatile("mov.u32 %0, %%clock;" : "=r"(t0));
    do { asm volatile("mov.u32 %0, %%clock;" : "=r"(t)); } while (t - t0 < n);
}
__device__ __forceinline__ void red_add64(unsigned long long* p, unsigned long long v) {
    asm volatile("red.relaxed.gpu.global.add.u64 [%0], %1;" ::"l"(p), "l"(v) : "memory");
}
__device__ __forceinline__ void ld_relaxed2x64(uint4& v, const void* p) {
    asm volatile("{\n.reg .b64 a, b;\nld.relaxed.gpu.global.v2.b64 {a, b}, [%4];\nmov.b64 {%0, %1}, a;\nmov.b64 {%2, %3}, b;\n}"
                 : "=r"(v.x), "=r"(v.y), "=r"(v.z), "=r"(v.w) : "l"(p) : "memory");
}
__device__ __forceinline__ void ld_relaxed128(uint4& v, const uint4* p) {
    asm volatile("ld.relaxed.gpu.global.v4.u32 {%0,%1,%2,%3}, [%4];" : "=r"(v.x), "=r"(v.y), "=r"(v.z), "=r"(v.w) : "l"(p) : "memory");
}
__device__ __forceinline__ uint32_t and3(uint32_t a, uint32_t b, uint32_t c) {
    uint32_t r;
    asm("lop3.b32 %0, %1, %2, %3, 0x80;" : "=r"(r) : "r"(a), "r"(b), "r"(c));
    return r;
}
__device__ __forceinline__ bool all_marked(const uint4& a, const uint4& b) {
    return __all_sync(~0u, and3(and3(a.x, a.y, a.z), and3(a.w, b.x, b.y), and3(b.z, b.w, 1u)));
}
__device__ __forceinline__ bool all_complete(const uint4& a, const uint4& b) {
    return __all_sync(~0u, and3(and3(a.x, a.z, b.x), b.z, 32u));
}
__device__ __forceinline__ float bf16_at(uint32_t a) {
    uint16_t v;
    asm volatile("ld.shared.u16 %0, [%1];" : "=h"(v) : "r"(a) : "memory");
    return __uint_as_float((uint32_t)v << 16);
}

__device__ __forceinline__ int bpos(int k) { return ((k >> 1) & 3) * 16 + ((k >> 4) & 3) * 4 + ((k >> 3) & 1) * 2 + (k & 1); }

__device__ __forceinline__ void gemv1_partial(const uint32_t* a1, uint32_t hb0, uint32_t hb1, int j, int c, uint32_t a) {
    float t0[4] = {0.f, 0.f, 0.f, 0.f}, t1[4] = {0.f, 0.f, 0.f, 0.f}, t2[4] = {0.f, 0.f, 0.f, 0.f}, t3[4] = {0.f, 0.f, 0.f, 0.f};
#pragma unroll
    for (int k = 0; k < 2; k++) {
        const uint32_t m0 = (j == k) ? hb0 : 0u, m1 = (j == k) ? hb1 : 0u;
        const uint32_t n0 = (j == k + 2) ? hb0 : 0u, n1 = (j == k + 2) ? hb1 : 0u;
        mma_bf16(t0, a1[8 * k], a1[8 * k + 1], a1[8 * k + 2], a1[8 * k + 3], m0, m1);
        mma_bf16(t1, a1[8 * k + 4], a1[8 * k + 5], a1[8 * k + 6], a1[8 * k + 7], m0, m1);
        mma_bf16(t2, a1[8 * k + 16], a1[8 * k + 17], a1[8 * k + 18], a1[8 * k + 19], n0, n1);
        mma_bf16(t3, a1[8 * k + 20], a1[8 * k + 21], a1[8 * k + 22], a1[8 * k + 23], n0, n1);
    }
    const bool up2 = c & 2, up1 = c & 1;
    float r4[4], r2[2];
    const float send[4] = {up2 ? t2[0] : t0[1], up2 ? t2[2] : t0[3], up2 ? t3[0] : t1[1], up2 ? t3[2] : t1[3]};
    const float keep[4] = {up2 ? t2[1] : t0[0], up2 ? t2[3] : t0[2], up2 ? t3[1] : t1[0], up2 ? t3[3] : t1[2]};
#pragma unroll
    for (int i = 0; i < 4; i++) r4[i] = keep[i] + __shfl_xor_sync(~0u, send[i], 2);
#pragma unroll
    for (int i = 0; i < 2; i++) r2[i] = (up1 ? r4[i + 2] : r4[i]) + __shfl_xor_sync(~0u, up1 ? r4[i] : r4[i + 2], 1);
    sts32(a, __float_as_uint(r2[0]));
    sts32(a + 32, __float_as_uint(r2[1]));
}

__device__ __forceinline__ float sum8(uint32_t a) {
    float p[8];
#pragma unroll
    for (int w = 0; w < 8; w++) p[w] = __uint_as_float(lds32(a + w * 256));
    return ((p[0] + p[1]) + (p[2] + p[3])) + ((p[4] + p[5]) + (p[6] + p[7]));
}

struct Maps { CUtensorMap v, wq, wo, w1, w2; };

__global__ void __cluster_dims__(2, 1, 1) __launch_bounds__(NTHREADS, 1)
decode_block_kernel(const __grid_constant__ Maps tm,
                    const __nv_bfloat16* __restrict__ x, const __nv_bfloat16* __restrict__ Kc,
                    const __nv_bfloat16* __restrict__ b1, const __nv_bfloat16* __restrict__ b2,
                    __nv_bfloat16* __restrict__ out, Scratch* __restrict__ scr, uint32_t tile_ns_x16) {
    unsigned long long* const g_acc1 = scr->acc1;
    unsigned int* const g_tick = scr->tick;
    uint4* const g_part = scr->part;
    extern __shared__ unsigned char smem_raw[];
    const uint32_t sb = ((uint32_t)__cvta_generic_to_shared(smem_raw) + 1023u) & ~1023u;
    const uint32_t bar_full = sb + OFF_BAR, bar_empty = bar_full + NST * 8;
    const uint32_t bar_q = bar_empty + NST * 8, bar_ml = bar_q + 8, bar_o = bar_ml + 8, bar_end = bar_o + 8, bar_go = bar_end + 8;

    const char* ksrc = (const char*)Kc + (size_t)blockIdx.x * (KEYS_PER_CTA * DH * 2);
    constexpr uint64_t pol = 0x12F0000000000000ull;
    if ((threadIdx.x & ~32) == 0) {
        const int k = threadIdx.x >> 5;
        mbar_init(bar_full + (T_K0 + k) * 8, 1);
        asm volatile("fence.mbarrier_init.release.cluster;" ::: "memory");
        mbar_expect_tx(bar_full + (T_K0 + k) * 8, TILE_BYTES);
        bulk_load_stream(sb + OFF_RING + (T_K0 + k) * TILE_BYTES, ksrc + k * TILE_BYTES, TILE_BYTES, bar_full + (T_K0 + k) * 8, pol);
    }
    int tid = threadIdx.x;
    asm volatile("" : "+r"(tid));
    const int lane = tid & 31;
    const int warp = __shfl_sync(~0u, tid >> 5, 0);
    const int bh = blockIdx.x >> 1, rank = blockIdx.x & 1;
    const int b = bh >> 5, h = bh & 31;
    const bool is_mlp = (rank == 0) && (bh < NMLP);
    const int f0 = bh * 32;

    if (elect_one()) {
        if (warp < 6) {
            if (warp >= 2) {
                const int s = T_WQ + warp - 2;
                mbar_init(bar_full + s * 8, 1);
                asm volatile("fence.mbarrier_init.release.cluster;" ::: "memory");
                mbar_expect_tx(bar_full + s * 8, TILE_BYTES);
                tma2d(sb + OFF_RING + s * TILE_BYTES, &tm.wq, h * DH + rank * 64, s * 128, bar_full + s * 8);
            }
        } else if (warp == 7) {
#pragma unroll
            for (int s = 0; s < NST; s++) mbar_init(bar_empty + s * 8, 8);
            asm volatile("fence.mbarrier_init.release.cluster;" ::: "memory");
        } else if (warp == 8) {
#pragma unroll
            for (int s = T_K0 + 2; s < NST; s++) mbar_init(bar_full + s * 8, 1);
            asm volatile("fence.mbarrier_init.release.cluster;" ::: "memory");
#pragma unroll
            for (int s = T_K0 + 2; s < T_K0 + NINIT; s++) {
                mbar_expect_tx(bar_full + s * 8, TILE_BYTES);
                bulk_load_stream(sb + OFF_RING + s * TILE_BYTES, ksrc + (size_t)(s - T_K0) * TILE_BYTES, TILE_BYTES, bar_full + s * 8, pol);
            }
        } else if (warp == 9) {
            mbar_init(bar_q, 2); mbar_init(bar_ml, 1); mbar_init(bar_o, 10); mbar_init(bar_end, 1); mbar_init(bar_go, 1);
            asm volatile("fence.mbarrier_init.release.cluster;" ::: "memory");
            mbar_expect_tx(bar_q, 128);
            mbar_expect_tx(bar_ml, is_mlp ? 8 + 2048 + 1024 + 64 : 8);
            if (is_mlp) {
                bulk_load(sb + OFF_X, x, 2048, bar_ml);
                bulk_load(sb + OFF_X + 2048, b2, 1024, bar_ml);
                bulk_load(sb + OFF_X + 3072, b1 + f0, 64, bar_ml);
            }
            mbar_expect_tx(bar_o, 512);
            asm volatile("prefetch.tensormap [%0];" ::"l"(&tm.wo) : "memory");
            asm volatile("prefetch.tensormap [%0];" ::"l"(&tm.v) : "memory");
            asm volatile("prefetch.tensormap [%0];" ::"l"(&tm.w1) : "memory");
            asm volatile("prefetch.tensormap [%0];" ::"l"(&tm.w2) : "memory");
        }
    }
    __syncwarp();
    asm volatile("barrier.cluster.arrive.relaxed.aligned;" ::: "memory");

    if (warp == 8) {
        const uint32_t t_start = gtime32();
        asm volatile("barrier.cluster.wait.aligned;" ::: "memory");
        if (lane == 0) {
#pragma unroll
            for (int w = 0; w < 4; w++) mbar_wait(bar_full + (T_WQ + w) * 8, 0);
#pragma unroll
            for (int k = NINIT; k < KPRE; k++) {
                const uint32_t fb = bar_full + (T_K0 + k) * 8;
                mbar_expect_tx(fb, TILE_BYTES);
                bulk_load_stream(sb + OFF_RING + (T_K0 + k) * TILE_BYTES, ksrc + (size_t)k * TILE_BYTES, TILE_BYTES, fb, pol);
            }
            const int vline0 = (bh * SK + rank * KEYS_PER_CTA) * 2;
            const int tend = is_mlp ? T_END : T_W1;
            const int lead16 = LEAD * 16 + (bh < NMLP ? SKEW : -2 * SKEW);
            int st = 0, ph = 0;
#pragma unroll 1
            for (int t = NST; t < tend; t++) {
                const uint32_t dst = sb + OFF_RING + st * TILE_BYTES, fb = bar_full + st * 8;
                mbar_wait(bar_empty + st * 8, ph);
                wait_until(t_start, ((t * 16 - lead16) * tile_ns_x16) >> 8);
                if (t == T_W1) {
                    mbar_wait(bar_full + ((T_W1 - 1 - WLATE) % NST) * 8, ((T_W1 - 1 - WLATE) / NST) & 1);
                }
                mbar_expect_tx(fb, TILE_BYTES);
                if (t < T_K1) {
                    tma2d(dst, &tm.wo, rank * 256 + (t - T_WO) * 64, h * DH, fb);
                } else if (t < T_V) {
                    bulk_load_stream(dst, ksrc + (size_t)(t - 8) * TILE_BYTES, TILE_BYTES, fb, pol);
                } else if (t < T_W1) {
                    tma2d_stream(dst, &tm.v, 0, vline0 + (t - T_V) * (TILE_KEYS * 2), fb, pol);
                } else if (t < T_W2) {
                    tma2d(dst, &tm.w1, f0, (t - T_W1) * 256, fb);
                } else {
#pragma unroll
                    for (int i = 0; i < 4; i++) tma2d(dst + i * 4096, &tm.w2, ((t - T_W2) * 4 + i) * 64, f0, fb);
                }
                if (++st == NST) { st = 0; ph ^= 1; }
            }
        }
        if (is_mlp) {
            __syncwarp();
            const int rr = lane & 7, mi = lane >> 3;
            float cs[4][4];
#pragma unroll
            for (int i = 0; i < 4; i++) cs[i][0] = cs[i][1] = cs[i][2] = cs[i][3] = 0.f;
#pragma unroll
            for (int t = 0; t < 2; t++) {
                const uint32_t a = sb + OFF_RING + (T_W1 % NST + t) * TILE_BYTES + ((mi >> 1) * 8 + rr) * 64 + ((mi & 1) ^ (rr >> 1)) * 16;
                mbar_wait(bar_full + (T_W1 % NST + t) * 8, (T_W1 / NST) & 1);
#pragma unroll 4
                for (int k = 0; k < 16; k += 2) {
                    uint32_t w[4][4];
                    ldsm4t(w[0], a + k * 1024); ldsm4t(w[1], (a ^ 32) + k * 1024);
                    ldsm4t(w[2], a + k * 1024 + 1024); ldsm4t(w[3], (a ^ 32) + k * 1024 + 1024);
#pragma unroll
                    for (int i = 0; i < 4; i++) mma_bf16(cs[i], w[i][0], w[i][1], w[i][2], w[i][3], 0x3f803f80u, 0x3f803f80u);
                }
            }
            const int c = lane & 3;
            const float lo = (c & 1) ? cs[0][2] + cs[2][2] : cs[0][0] + cs[2][0], hi = (c & 1) ? cs[1][2] + cs[3][2] : cs[1][0] + cs[3][0];
            sts32(sb + OFF_CS + (c * 8 + (lane >> 2)) * 4, __float_as_uint((c & 2) ? hi : lo));
            asm volatile("bar.arrive 2, 288;" ::: "memory");
        }
        return;
    }

    if (warp == 9) {
        if (is_mlp) {
#pragma unroll
            for (int i = 0; i < 8; i++) g_part[((i * 4 + (lane >> 3)) * NMLP + bh) * 8 + (lane & 7)] = make_uint4(0, 0, 0, 0);
            __threadfence();
        }
        asm volatile("barrier.cluster.wait.aligned;" ::: "memory");
        if (lane == 0) mbar_arrive(bar_o);
        if (is_mlp) {
            mbar_wait(bar_end, 0);
            for (int n = 0;; n++) {
                unsigned v = 0;
                if (lane < 8) asm volatile("ld.relaxed.gpu.global.u32 %0, [%1];" : "=r"(v) : "l"(g_tick + lane * 32) : "memory");
                if (__reduce_add_sync(~0u, v) >= NCTA) break;
                if (n > SPIN_LIMIT) __trap();
            }
            if (lane == 0) mbar_arrive(bar_go);
        }
        return;
    }

    const int g = lane >> 2, c = lane & 3;
    const int rr = lane & 7, mi = lane >> 3;
    const int mb_ = g & 1, j4 = g >> 1;
    const int d0 = warp * 64 + j4 * 16 + c * 2;
    uint32_t qa[16], wf[64];
    {
        if (warp == 6) {
            const uint4 xa0 = __ldg((const uint4*)(x + b * D_MODEL) + lane), xa1 = __ldg((const uint4*)(x + b * D_MODEL) + 32 + lane);
            const uint32_t xa[8] = {xa0.x, xa0.y, xa0.z, xa0.w, xa1.x, xa1.y, xa1.z, xa1.w};
            float s = 0.f;
#pragma unroll
            for (int i = 0; i < 8; i++) s += bf_lo(xa[i]) + bf_hi(xa[i]);
#pragma unroll
            for (int o = 16; o; o >>= 1) s += __shfl_xor_sync(~0u, s, o);
            const float mean = s * (1.0f / D_MODEL);
            float v = 0.f;
#pragma unroll
            for (int i = 0; i < 8; i++) { const float e0 = bf_lo(xa[i]) - mean, e1 = bf_hi(xa[i]) - mean; v += e0 * e0 + e1 * e1; }
#pragma unroll
            for (int o = 16; o; o >>= 1) v += __shfl_xor_sync(~0u, v, o);
            const float mb = rnd_bf(mean);
            const float den = rnd_bf(sqrtf(rnd_bf(rnd_bf(v * (1.0f / D_MODEL)) + 1e-5f)));
#pragma unroll
            for (int i = 0; i < 8; i++) {
                const int k = (i >> 2) * 256 + lane * 8 + (i & 3) * 2;
                sts32(sb + OFF_XN + ((k & ~63) + bpos(k)) * 2,
                      pack_bf(__fdiv_rn(rnd_bf(bf_lo(xa[i]) - mb), den), __fdiv_rn(rnd_bf(bf_hi(xa[i]) - mb), den)));
            }
        }
        asm volatile("barrier.cluster.wait.aligned;" ::: "memory");
        cons_sync();

        float q0[4] = {0.f, 0.f, 0.f, 0.f}, q1[4] = {0.f, 0.f, 0.f, 0.f};
        const uint32_t aoff = ((warp >> 2) * 64 + (mi >> 1) * 8 + rr) * 128 + (((warp & 3) * 2 + (mi & 1)) ^ rr) * 16;
#pragma unroll
        for (int t = 0; t < 4; t++) {
            const uint32_t xaddr = sb + OFF_XN + (t * 2 + (warp >> 2)) * 128 + c * 32;
            const uint4 p0 = lds128(xaddr), p1 = lds128(xaddr + 16);
            const uint32_t base = sb + OFF_RING + (T_WQ + t) * TILE_BYTES + aoff;
            mbar_wait(bar_full + (T_WQ + t) * 8, 0);
            uint32_t a0[4], a1[4], a2[4], a3[4];
            ldsm4t(a0, base); ldsm4t(a1, base + 2048); ldsm4t(a2, base + 4096); ldsm4t(a3, base + 6144);
            mma_bf16(q0, a0[0], a0[1], a0[2], a0[3], p0.x, p0.y);
            mma_bf16(q1, a1[0], a1[1], a1[2], a1[3], p0.z, p0.w);
            mma_bf16(q0, a2[0], a2[1], a2[2], a2[3], p1.x, p1.y);
            mma_bf16(q1, a3[0], a3[1], a3[2], a3[3], p1.z, p1.w);
            __syncwarp();
            if (lane == 0) mbar_arrive(bar_empty + (T_WQ + t) * 8);
        }
        if (c < 2) sts32(sb + OFF_PART + (warp * 16 + c * 8 + g) * 4, __float_as_uint(c ? q0[2] + q1[2] : q0[0] + q1[0]));
        cons_sync();
        if (warp == 0) {
            const uint2 u = lds64(sb + OFF_PART + lane * 8), w = lds64(sb + OFF_PART + 256 + lane * 8);
            const uint32_t qq = pack_bf(__uint_as_float(u.x) + __uint_as_float(w.x), __uint_as_float(u.y) + __uint_as_float(w.y));
            const uint32_t dst = sb + OFF_Q + rank * 128 + lane * 4;
            sts32(dst, qq);
            st_async_b32(mapa(dst, rank ^ 1), qq, mapa(bar_q, rank ^ 1));
            __syncwarp();
            if (lane == 0) mbar_arrive(bar_q);
        }
        mbar_wait(bar_q, 0);
#pragma unroll
        for (int j = 0; j < 16; j++) qa[j] = lds32(sb + OFF_Q + ((j & 8) + ((g + j) & 7)) * 16 + c * 4);
    }

    int st = T_K0, ph = 0;
    float mx = -INFINITY;
    {
        uint32_t koff0 = sb + OFF_RING + (warp * 8 + rr) * 256 + ((rr + mi) & 7) * 16;
        uint32_t koff1 = sb + OFF_RING + (warp * 8 + rr) * 256 + ((rr + mi + 4) & 7) * 16;
        asm volatile("" : "+r"(koff0), "+r"(koff1));
        const bool valid = (c == (g >> 1));
        uint32_t spos = sb + OFF_SP + bpos(warp * 8 + g) * 2;
        auto k_tiles = [&](int n) {
#pragma unroll 1
            for (int i = 0; i < n; i++) {
                const uint32_t base = st * TILE_BYTES;
                mbar_wait(bar_full + st * 8, ph);
                uint32_t k0[4], k1[4], k2[4], k3[4];
                ldsm4(k0, base + koff0); ldsm4(k1, base + koff1);
                ldsm4(k2, base + koff0 + 128); ldsm4(k3, base + koff1 + 128);
                float s0[4] = {0.f, 0.f, 0.f, 0.f}, s1[4] = {0.f, 0.f, 0.f, 0.f};
                mma_bf16(s0, qa[0], qa[2], qa[1], qa[3], k0[0], k0[1]);
                mma_bf16(s1, qa[0], qa[2], qa[1], qa[3], k0[2], k0[3]);
                mma_bf16(s0, qa[4], qa[6], qa[5], qa[7], k1[0], k1[1]);
                mma_bf16(s1, qa[4], qa[6], qa[5], qa[7], k1[2], k1[3]);
                mma_bf16(s0, qa[8], qa[10], qa[9], qa[11], k2[0], k2[1]);
                mma_bf16(s1, qa[8], qa[10], qa[9], qa[11], k2[2], k2[3]);
                mma_bf16(s0, qa[12], qa[14], qa[13], qa[15], k3[0], k3[1]);
                mma_bf16(s1, qa[12], qa[14], qa[13], qa[15], k3[2], k3[3]);
                __syncwarp();
                if (lane == 0) mbar_arrive(bar_empty + st * 8);
                const float raw = (g & 1) ? s0[1] + s1[3] : s0[0] + s1[2];
                const uint32_t sc = pack_bf(rnd_bf(raw) * 0.08838834764831845f, 0.f);
                if (valid) { sts16(spos, (uint16_t)sc); mx = fmaxf(mx, bf_lo(sc)); }
                spos += TILE_KEYS * 2;
                if (++st == NST) { st = 0; ph ^= 1; }
            }
        };
        k_tiles(KPRE);
        {
            static_assert(T_WO == NST, "wo tiles sit in slots 0..3, second pass");
            const int s = warp >> 1;
            const int row = (mi >> 1) * 4 + (rr >> 1) + (rr & 1) * 8;
            const uint32_t base = sb + OFF_RING + s * TILE_BYTES + row * 128;
            const uint32_t c0 = (((mi & 1) * 2 + (warp & 1)) ^ (row & 7)) * 16, c1 = c0 ^ 64;
            mbar_wait(bar_full + s * 8, 1);
#pragma unroll
            for (int t = 0; t < 8; t++) {
                ldsm4t(*(uint32_t(*)[4])(wf + 8 * t), base + t * 2048 + c0);
                ldsm4t(*(uint32_t(*)[4])(wf + 8 * t + 4), base + t * 2048 + c1);
            }
            __syncwarp();
            if (lane < 4) mbar_arrive(bar_empty + lane * 8);
            st = 4;
        }
        k_tiles(NTILE - KPRE);
    }
    {
#pragma unroll
        for (int o = 16; o; o >>= 1) mx = fmaxf(mx, __shfl_xor_sync(~0u, mx, o));
        if (lane == 0) sts32(sb + OFF_RED + warp * 4, __float_as_uint(mx));
        cons_sync();
        const uint4 m0 = lds128(sb + OFF_RED), m1 = lds128(sb + OFF_RED + 16);
        const float mloc = fmaxf(fmaxf(fmaxf(__uint_as_float(m0.x), __uint_as_float(m0.y)), fmaxf(__uint_as_float(m0.z), __uint_as_float(m0.w))),
                                 fmaxf(fmaxf(__uint_as_float(m1.x), __uint_as_float(m1.y)), fmaxf(__uint_as_float(m1.z), __uint_as_float(m1.w))));
        const uint4 s0 = lds128(sb + OFF_SP + tid * 16), s1 = lds128(sb + OFF_SP + 4096 + tid * 16);
        const uint32_t sv[8] = {s0.x, s0.y, s0.z, s0.w, s1.x, s1.y, s1.z, s1.w};
        constexpr float LOG2E = 1.4426950408889634f;
        float l = 0.f;
#pragma unroll
        for (int i = 0; i < 8; i++) l += exp2f((bf_lo(sv[i]) - mloc) * LOG2E) + exp2f((bf_hi(sv[i]) - mloc) * LOG2E);
#pragma unroll
        for (int o = 16; o; o >>= 1) l += __shfl_xor_sync(~0u, l, o);
        if (lane == 0) sts32(sb + OFF_RED + 32 + warp * 4, __float_as_uint(l));
        cons_sync();
        const uint4 l0 = lds128(sb + OFF_RED + 32), l1 = lds128(sb + OFF_RED + 48);
        const float lloc = ((__uint_as_float(l0.x) + __uint_as_float(l0.y)) + (__uint_as_float(l0.z) + __uint_as_float(l0.w))) +
                           ((__uint_as_float(l1.x) + __uint_as_float(l1.y)) + (__uint_as_float(l1.z) + __uint_as_float(l1.w)));
        if (tid == 0) st_async_v2(mapa(sb + OFF_ML, rank ^ 1), __float_as_uint(mloc), __float_as_uint(lloc), mapa(bar_ml, rank ^ 1));
        mbar_wait(bar_ml, 0);
        const uint2 pml = lds64(sb + OFF_ML);
        const float mp = __uint_as_float(pml.x), lp = __uint_as_float(pml.y);
        const float M = fmaxf(mloc, mp);
        const float m_a = rank ? mp : mloc, l_a = rank ? lp : lloc, m_b = rank ? mloc : mp, l_b = rank ? lloc : lp;
        const float L = l_a * exp2f((m_a - M) * LOG2E) + l_b * exp2f((m_b - M) * LOG2E);
        const float inv = 1.0f / L;
        uint32_t pv[8];
#pragma unroll
        for (int i = 0; i < 8; i++)
            pv[i] = pack_bf(exp2f((bf_lo(sv[i]) - M) * LOG2E) * inv, exp2f((bf_hi(sv[i]) - M) * LOG2E) * inv);
        sts128(sb + OFF_SP + tid * 16, make_uint4(pv[0], pv[1], pv[2], pv[3]));
        sts128(sb + OFF_SP + 4096 + tid * 16, make_uint4(pv[4], pv[5], pv[6], pv[7]));
        cons_sync();
    }
    unsigned long long* acc1_dst = g_acc1 + b * D_MODEL + rank * 256 + warp * 32 + c * 8 + g;
    uint32_t o_dst = sb + OFF_O + (rank * 2 + (c & 1)) * O_STRIDE + (warp * 8 + g) * 4, o_bar = bar_o;
    if (c & 2) { o_dst = mapa(o_dst, rank ^ 1); o_bar = mapa(bar_o, rank ^ 1); }
    uint32_t o_src = sb + OFF_O + (rr & 3) * O_STRIDE + mi * 16;
    unsigned* tick_dst = g_tick + (bh & 7) * 32;
    asm volatile("" : "+l"(acc1_dst), "+l"(tick_dst), "+r"(o_dst), "+r"(o_bar), "+r"(o_src));
    const bool is_fin = bh < NFIN;
    const unsigned long long* p1 = g_acc1 + mb_ * D_MODEL + warp * 64 + j4 * 8 + c * 2;
    uint4* part_dst = g_part + ((warp * 4 + c) * NMLP + bh) * 8 + g;
    const uint4* inbox = g_part + bh * (NMLP * 8) + tid;
    const uint4* inbox2 = tid < (NMLP - 32) * 8 ? inbox + 256 : inbox;
    float wsel = tid < (NMLP - 32) * 8 ? 1.0f : 0.0f;
    __nv_bfloat16* out_dst = out + ((lane >> 3) & 1) * D_MODEL + bh * 16 + (lane >> 4) * 8 + (lane & 7);
    asm volatile("" : "+l"(p1), "+l"(part_dst), "+l"(inbox), "+l"(inbox2), "+f"(wsel), "+l"(out_dst));
    uint32_t xv[2] = {lds32(sb + OFF_X + (mb_ * D_MODEL + d0) * 2), lds32(sb + OFF_X + (mb_ * D_MODEL + d0 + 8) * 2)};
    float b1v = bf16_at(sb + OFF_X + 3072 + lane * 2);
    float b2v = bf16_at(sb + OFF_X + 2048 + ((bh & 31) * 16 + (lane >> 4) * 8 + (lane & 7)) * 2);
    uint32_t a_part = sb + OFF_PART + warp * 256 + ((c >> 1) * 32 + (c & 1) * 16 + g) * 4;
    uint32_t a_stat = sb + OFF_STAT + (mb_ * 16 + (c & 1) * 8 + warp) * 4;
    uint32_t a_keep = sb + OFF_RED + mb_ * 32 + c * 4;
    uint32_t a_sum = sb + OFF_PART + (warp * 32 + lane) * 4, a_cs = sb + OFF_CS + lane * 4;
    uint32_t a_hid = sb + OFF_HID + warp * 80 + lane * 2, a_hidb = sb + OFF_HID + (rr & 1) * 80 + mi * 16;
    uint32_t a_fin = sb + OFF_PART + warp * 256 + lane * 4;
    uint32_t a_hfin = sb + OFF_RED + ((lane >> 3) & 1) * 32 + ((lane >> 4) * 8 + (lane & 7)) * 2;
    int keep_h = warp * 4 + j4 == bh;
    asm volatile("" : "+r"(a_part), "+r"(a_stat), "+r"(a_keep), "+r"(a_sum), "+r"(a_cs), "+r"(a_hid), "+r"(a_hidb), "+r"(a_fin), "+r"(a_hfin),
                 "+r"(keep_h), "+f"(b1v), "+f"(b2v));
    static_assert(T_W1 % NST + 3 < NST, "w1/w2 occupy four consecutive slots with the same parity");
    constexpr int W_PAR = (T_W1 / NST) & 1;
    uint32_t w1_bar = bar_full + (T_W1 % NST + (warp >> 2)) * 8;
    uint32_t w1_a = sb + OFF_RING + (T_W1 % NST + (warp >> 2)) * TILE_BYTES + ((warp & 3) * 64 + (mi >> 1) * 8 + rr) * 64 + ((mi & 1) ^ (rr >> 1)) * 16;
    uint32_t w2_a = sb + OFF_RING + (T_W2 % NST + (warp >> 2)) * TILE_BYTES + (warp & 3) * 4096 + ((mi >> 1) * 8 + rr) * 128 + ((mi & 1) ^ rr) * 16;
    asm volatile("" : "+r"(w1_bar), "+r"(w1_a), "+r"(w2_a));
    {
        const int hh = warp >> 2, ch = 2 * (warp & 3);
        const int line = 2 * (8 * (mi >> 1) + rr) + hh;
        uint32_t voff = sb + OFF_RING + line * 128 + (((ch ^ (mi & 1) ^ (rr >> 2)) ^ (line & 7)) * 16);
        uint32_t pmask = ((c >> 1) == (g & 1)) ? 0xffffffffu : 0u;
        asm volatile("" : "+r"(voff), "+r"(pmask));
        uint32_t paddr = sb + OFF_SP + c * 32;
        float o0[4] = {0.f, 0.f, 0.f, 0.f}, o1[4] = {0.f, 0.f, 0.f, 0.f};
#pragma unroll 1
        for (int i = 0; i < NTILE; i++) {
            const uint32_t base = voff + st * TILE_BYTES;
            uint4 p0 = lds128(paddr), p1 = lds128(paddr + 16);
            p0.x &= pmask; p0.y &= pmask; p0.z &= pmask; p0.w &= pmask;
            p1.x &= pmask; p1.y &= pmask; p1.z &= pmask; p1.w &= pmask;
            asm volatile("" : "+r"(p0.x), "+r"(p0.y), "+r"(p0.z), "+r"(p0.w), "+r"(p1.x), "+r"(p1.y), "+r"(p1.z), "+r"(p1.w));
            mbar_wait(bar_full + st * 8, ph);
            uint32_t a0[4], a1[4], a2[4], a3[4];
            ldsm4t(a0, base); ldsm4t(a1, base + 4096); ldsm4t(a2, base + 8192); ldsm4t(a3, base + 12288);
            if (i == NTILE - 1 && tid == 0) {
                asm volatile("red.relaxed.gpu.global.add.u32 [%0], 1;" ::"l"(tick_dst) : "memory");
                mbar_arrive(bar_end);
            }
            mma_bf16(o0, a0[0], a0[1], a0[2], a0[3], p0.x, p0.y);
            mma_bf16(o1, a1[0], a1[1], a1[2], a1[3], p0.z, p0.w);
            mma_bf16(o0, a2[0], a2[1], a2[2], a2[3], p1.x, p1.y);
            mma_bf16(o1, a3[0], a3[1], a3[2], a3[3], p1.z, p1.w);
            __syncwarp();
            if (lane == 0) mbar_arrive(bar_empty + st * 8);
            paddr += TILE_KEYS * 2;
            if (++st == NST) { st = 0; ph ^= 1; }
        }
        const float v0 = (o0[0] + o1[0]) + (o0[3] + o1[3]);
        const float v1 = (o0[1] + o1[1]) + (o0[2] + o1[2]);
        const uint32_t hi = pack_bf(v0, v1);
        const uint32_t val = (c & 1) ? pack_bf(v0 - bf_lo(hi), v1 - bf_hi(hi)) : hi;
        if (c & 2) st_async_b32(o_dst, val, o_bar);
        else sts32(o_dst, val);
        __syncwarp();
        if (lane == 0) mbar_arrive(bar_o);
        mbar_wait(bar_o, 0);
    }
    {
        float d00[4] = {0.f, 0.f, 0.f, 0.f}, d01[4] = {0.f, 0.f, 0.f, 0.f}, d10[4] = {0.f, 0.f, 0.f, 0.f}, d11[4] = {0.f, 0.f, 0.f, 0.f};
        uint32_t ob[4][4];
#pragma unroll
        for (int t = 0; t < 4; t++) ldsm4(ob[t], o_src + t * 64);
#pragma unroll
        for (int t = 0; t < 4; t++) {
            mma_bf16(d00, wf[16 * t], wf[16 * t + 1], wf[16 * t + 2], wf[16 * t + 3], ob[t][0], ob[t][1]);
            mma_bf16(d10, wf[16 * t + 4], wf[16 * t + 5], wf[16 * t + 6], wf[16 * t + 7], ob[t][0], ob[t][1]);
            mma_bf16(d01, wf[16 * t + 8], wf[16 * t + 9], wf[16 * t + 10], wf[16 * t + 11], ob[t][2], ob[t][3]);
            mma_bf16(d11, wf[16 * t + 12], wf[16 * t + 13], wf[16 * t + 14], wf[16 * t + 15], ob[t][2], ob[t][3]);
        }
        const float e0 = (d00[0] + d01[0]) + (d00[1] + d01[1]), e1 = (d00[2] + d01[2]) + (d00[3] + d01[3]);
        const float e2 = (d10[0] + d11[0]) + (d10[1] + d11[1]), e3 = (d10[2] + d11[2]) + (d10[3] + d11[3]);
        const float ea = (c & 2) ? e2 : e0, eb = (c & 2) ? e3 : e1;
        const float e = ((c & 1) ? eb : ea) + __shfl_xor_sync(~0u, (c & 1) ? ea : eb, 1);
        red_add64(acc1_dst, fx_encode(e));
    }
    if (!is_mlp) return;

    {
        uint32_t* a1 = wf;
        uint32_t* a2 = wf + 32;
        auto load_w1 = [&]() {
#pragma unroll
            for (int k = 0; k < 4; k++) {
                ldsm4t(*(uint32_t(*)[4])(a1 + 8 * k), w1_a + k * 1024);
                ldsm4t(*(uint32_t(*)[4])(a1 + 8 * k + 4), (w1_a ^ 32) + k * 1024);
            }
        };
        auto load_w2 = [&]() {
#pragma unroll
            for (int u = 0; u < 2; u++)
#pragma unroll
                for (int T = 0; T < 4; T++) ldsm4t(*(uint32_t(*)[4])(a2 + 16 * u + 4 * T), (w2_a ^ (T * 32)) + u * 2048);
        };
        uint32_t hb0, hb1;
        int stage = 0;
        {
            uint4 ua = make_uint4(0, 0, 0, 0), ub = ua;
            int n = 0, polled = 0;
#pragma unroll 1
            do {
                if (!polled && __all_sync(~0u, mbar_test(bar_go, 0))) {
                    ld_relaxed2x64(ua, p1); ld_relaxed2x64(ub, p1 + 32);
                    polled = 1;
                }
                if (stage < 2 && __all_sync(~0u, mbar_test(w1_bar + stage * 16, W_PAR))) {
                    if (stage == 0) load_w1(); else load_w2();
                    stage++;
                }
                if (++n > SPIN_LIMIT * 16) __trap();
            } while (stage < 1 || !polled);
            if (stage < 2 && __all_sync(~0u, mbar_test(w1_bar + 16, W_PAR))) { load_w2(); stage = 2; }
            n = 0;
            while (!all_complete(ua, ub)) {
                ld_relaxed2x64(ua, p1); ld_relaxed2x64(ub, p1 + 32);
                if (++n > SPIN_LIMIT) __trap();
            }
            const uint32_t at0 = pack_bf(fx_decode(ua.x, ua.y), fx_decode(ua.z, ua.w)), at1 = pack_bf(fx_decode(ub.x, ub.y), fx_decode(ub.z, ub.w));
            hb0 = pack_bf(bf_lo(xv[0]) + bf_lo(at0), bf_hi(xv[0]) + bf_hi(at0));
            hb1 = pack_bf(bf_lo(xv[1]) + bf_lo(at1), bf_hi(xv[1]) + bf_hi(at1));
        }
        gemv1_partial(a1, hb0, hb1, j4, c, a_part);
        {
            const float h0 = bf_lo(hb0), h1 = bf_hi(hb0), h2 = bf_lo(hb1), h3 = bf_hi(hb1);
            const float s1 = (h0 + h1) + (h2 + h3);
            const float s2 = (h0 * h0 + h1 * h1) + (h2 * h2 + h3 * h3);
            float t = ((c & 1) ? s2 : s1) + __shfl_xor_sync(~0u, (c & 1) ? s1 : s2, 1);
            t += __shfl_xor_sync(~0u, t, 2);
            t += __shfl_xor_sync(~0u, t, 8);
            t += __shfl_xor_sync(~0u, t, 16);
            if ((lane & 0x1a) == 0) sts32(a_stat, __float_as_uint(t));
        }
        if (keep_h) {
            sts32(a_keep, hb0);
            sts32(a_keep + 16, hb1);
        }
        asm volatile("bar.sync 2, 288;" ::: "memory");
        if (warp < 2) {
            const uint4 q0 = lds128(sb + OFF_STAT + warp * 64), q1 = lds128(sb + OFF_STAT + warp * 64 + 16);
            const uint4 q2 = lds128(sb + OFF_STAT + warp * 64 + 32), q3 = lds128(sb + OFF_STAT + warp * 64 + 48);
            const float sacc = sum8(a_sum);
            const float cs = __uint_as_float(lds32(a_cs));
            const float mean = (((__uint_as_float(q0.x) + __uint_as_float(q0.y)) + (__uint_as_float(q0.z) + __uint_as_float(q0.w))) +
                                ((__uint_as_float(q1.x) + __uint_as_float(q1.y)) + (__uint_as_float(q1.z) + __uint_as_float(q1.w)))) * (1.0f / D_MODEL);
            const float msq = (((__uint_as_float(q2.x) + __uint_as_float(q2.y)) + (__uint_as_float(q2.z) + __uint_as_float(q2.w))) +
                               ((__uint_as_float(q3.x) + __uint_as_float(q3.y)) + (__uint_as_float(q3.z) + __uint_as_float(q3.w)))) * (1.0f / D_MODEL);
            const float var = fmaxf(msq - mean * mean, 0.f);
            float sq, iden;
            asm("sqrt.approx.ftz.f32 %0, %1;" : "=f"(sq) : "f"(rnd_bf(rnd_bf(var) + 1e-5f)));
            asm("rcp.approx.ftz.f32 %0, %1;" : "=f"(iden) : "f"(rnd_bf(sq)));
            const float z = fmaxf(rnd_bf(rnd_bf((sacc - rnd_bf(mean) * cs) * iden) + b1v), 0.f);
            sts16(a_hid, (uint16_t)pack_bf(z * z, 0.f));
        }
        if (stage < 2) { mbar_wait(w1_bar + 16, W_PAR); load_w2(); }
        cons_sync();
        uint32_t hb[4];
        ldsm4(hb, a_hidb);
        const float hfin = bf16_at(a_hfin);
        float y[4][4];
#pragma unroll
        for (int T = 0; T < 4; T++) {
            y[T][0] = y[T][1] = y[T][2] = y[T][3] = 0.f;
            mma_bf16(y[T], a2[4 * T], a2[4 * T + 1], a2[4 * T + 2], a2[4 * T + 3], hb[0], hb[1]);
        }
#pragma unroll
        for (int T = 0; T < 4; T++)
            mma_bf16(y[T], a2[16 + 4 * T], a2[16 + 4 * T + 1], a2[16 + 4 * T + 2], a2[16 + 4 * T + 3], hb[2], hb[3]);
        {
            const bool up2 = c & 2, up1 = c & 1;
            uint32_t e[4];
#pragma unroll
            for (int i = 0; i < 4; i++) e[i] = __float_as_uint(up2 ? (up1 ? y[3][i] : y[2][i]) : (up1 ? y[1][i] : y[0][i])) | 1u;
            asm volatile("st.relaxed.gpu.global.v4.u32 [%0], {%1,%2,%3,%4};" ::"l"(part_dst), "r"(e[0]), "r"(e[1]), "r"(e[2]), "r"(e[3]) : "memory");
        }
        if (!is_fin) return;
        {
            uint4 u, w;
            int n = 0;
            spin_cycles(DELAY2);
            do {
                ld_relaxed128(u, inbox); ld_relaxed128(w, inbox2);
                if (++n > SPIN_LIMIT) __trap();
            } while (!all_marked(u, w));
            const float v0 = fmaf(__uint_as_float(w.x), wsel, __uint_as_float(u.x)), v1 = fmaf(__uint_as_float(w.y), wsel, __uint_as_float(u.y));
            const float v2 = fmaf(__uint_as_float(w.z), wsel, __uint_as_float(u.z)), v3 = fmaf(__uint_as_float(w.w), wsel, __uint_as_float(u.w));
            const bool up16 = lane & 16, up8 = lane & 8;
            const float r0 = (up16 ? v2 : v0) + __shfl_xor_sync(~0u, up16 ? v0 : v2, 16);
            const float r1 = (up16 ? v3 : v1) + __shfl_xor_sync(~0u, up16 ? v1 : v3, 16);
            const float r = (up8 ? r1 : r0) + __shfl_xor_sync(~0u, up8 ? r0 : r1, 8);
            sts32(a_fin, __float_as_uint(r));
        }
        cons_sync();
        if (warp == 0) {
            const float y2 = sum8(a_sum);
            *out_dst = __ushort_as_bfloat16((unsigned short)pack_bf(hfin + rnd_bf(rnd_bf(y2) + b2v), 0.f));
        }
        if (bh == 0) {
            *(ulonglong2*)(g_acc1 + tid * 4) = make_ulonglong2(0, 0);
            *(ulonglong2*)(g_acc1 + tid * 4 + 2) = make_ulonglong2(0, 0);
            if (tid < 8) g_tick[tid * 32] = 0;
        }
    }
}

typedef CUresult (*EncodeFn)(CUtensorMap*, CUtensorMapDataType, cuuint32_t, void*, const cuuint64_t*, const cuuint64_t*,
                             const cuuint32_t*, const cuuint32_t*, CUtensorMapInterleave, CUtensorMapSwizzle,
                             CUtensorMapL2promotion, CUtensorMapFloatOOBfill);

void make_map(EncodeFn enc, CUtensorMap* tm, void* ptr, uint64_t cols, uint64_t rows, uint32_t box_cols, uint32_t box_rows,
              CUtensorMapSwizzle swz) {
    const cuuint64_t dims[2] = {cols, rows};
    const cuuint64_t strides[1] = {cols * 2};
    const cuuint32_t box[2] = {box_cols, box_rows};
    const cuuint32_t es[2] = {1, 1};
    enc(tm, CU_TENSOR_MAP_DATA_TYPE_BFLOAT16, 2, ptr, dims, strides, box, es, CU_TENSOR_MAP_INTERLEAVE_NONE, swz,
        CU_TENSOR_MAP_L2_PROMOTION_NONE, CU_TENSOR_MAP_FLOAT_OOB_FILL_NONE);
}

}

extern "C" void kernel_launch(void* const* d_in, const int* in_sizes, int n_in, void* d_out, int out_size) {
    (void)in_sizes; (void)n_in; (void)out_size;
    static EncodeFn enc = nullptr;
    static Scratch* scr = nullptr;
    static uint32_t tile_ns_x16 = 0;
    if (!enc) {
        void* fn = nullptr;
        cudaDriverEntryPointQueryResult qr;
        cudaGetDriverEntryPoint("cuTensorMapEncodeTiled", &fn, cudaEnableDefault, &qr);
        enc = (EncodeFn)fn;
        cudaGetSymbolAddress((void**)&scr, g_scratch);
        int dev = 0, mem_khz = 0, bus_bits = 0;
        cudaGetDevice(&dev);
        cudaDeviceGetAttribute(&mem_khz, cudaDevAttrMemoryClockRate, dev);
        cudaDeviceGetAttribute(&bus_bits, cudaDevAttrGlobalMemoryBusWidth, dev);
        const double bytes_per_ns = 2.0 * mem_khz * 1e-6 * (bus_bits / 8) * (PACE * 1e-3);
        if (bytes_per_ns > 0) tile_ns_x16 = (uint32_t)(16.0 * NCTA * TILE_BYTES / bytes_per_ns);
        cudaFuncSetAttribute(decode_block_kernel, cudaFuncAttributeMaxDynamicSharedMemorySize, SMEM_BYTES);
    }
    Maps tm;
    make_map(enc, &tm.v, d_in[2], 64, (uint64_t)2 * NHEAD * SK * 2, 64, TILE_KEYS * 2, CU_TENSOR_MAP_SWIZZLE_128B);
    make_map(enc, &tm.wq, d_in[3], QCOLS, D_MODEL, 64, 128, CU_TENSOR_MAP_SWIZZLE_128B);
    make_map(enc, &tm.wo, d_in[4], D_MODEL, QCOLS, 64, 128, CU_TENSOR_MAP_SWIZZLE_128B);
    make_map(enc, &tm.w1, d_in[6], FF, D_MODEL, 32, 256, CU_TENSOR_MAP_SWIZZLE_64B);
    make_map(enc, &tm.w2, d_in[8], D_MODEL, FF, 64, 32, CU_TENSOR_MAP_SWIZZLE_128B);
    decode_block_kernel<<<NCTA, NTHREADS, SMEM_BYTES>>>(
        tm, (const __nv_bfloat16*)d_in[0], (const __nv_bfloat16*)d_in[1], (const __nv_bfloat16*)d_in[7],
        (const __nv_bfloat16*)d_in[9], (__nv_bfloat16*)d_out, scr, tile_ns_x16);
}
```

```cpp
#include <cuda_runtime.h>
#include <cuda_bf16.h>
#include <cuda.h>
#include <stdint.h>

namespace {

constexpr int D_MODEL = 512;
constexpr int NHEAD = 32;
constexpr int SK = 8192;
constexpr int DH = 128;
constexpr int FF = 1376;
constexpr int QCOLS = NHEAD * DH;

constexpr int NCTA = 128;
constexpr int KEYS_PER_CTA = SK / 2;
constexpr int TILE_KEYS = 64;
constexpr int TILE_BYTES = TILE_KEYS * DH * 2;
constexpr int NTILE = KEYS_PER_CTA / TILE_KEYS;
constexpr int NST = 12;
constexpr int NINIT = 5;
constexpr int WLATE = 1;
constexpr int LEAD = 7;
constexpr int PACE = 958;
constexpr int SKEW = 8;
constexpr int DELAY2 = 300;
constexpr int NCONS = 256;
constexpr int NTHREADS = NCONS + 64;
constexpr int NMLP = FF / 32;
constexpr int KPRE = NST - 4;
constexpr int T_WQ = 0, T_K0 = 4, T_WO = T_K0 + KPRE, T_K1 = T_WO + 4, T_V = T_K1 + NTILE - KPRE, T_W1 = T_V + NTILE,
              T_W2 = T_W1 + 2, T_END = T_W2 + 2;

constexpr int OFF_RING = 0;
constexpr int OFF_SP = OFF_RING + NST * TILE_BYTES;
constexpr int OFF_PART = OFF_SP + KEYS_PER_CTA * 2;
constexpr int OFF_CS = OFF_PART + 8 * 64 * 4;
constexpr int OFF_XN = OFF_CS + 32 * 4;
constexpr int OFF_X = OFF_XN + 1024;
constexpr int OFF_OP = OFF_X + 2048 + 1024 + 64;
constexpr int OFF_O = OFF_OP + 512;
constexpr int OFF_Q = OFF_O + 256;
constexpr int OFF_RED = OFF_Q + 256;
constexpr int OFF_STAT = OFF_RED + 64;
constexpr int OFF_HID = OFF_STAT + 128;
constexpr int OFF_ML = OFF_HID + 160;
constexpr int OFF_BAR = OFF_ML + 16;
constexpr int SMEM_USED = OFF_BAR + (2 * NST + 5) * 8;
constexpr int SMEM_BYTES = SMEM_USED + 1024;

constexpr float FX_SCALE = 1073741824.0f;
constexpr float FX_INV = 1.0f / 1073741824.0f;

constexpr int NFIN = 32;
struct Scratch {
    unsigned long long acc1[2 * D_MODEL];
    unsigned int tick[8 * 32];
    uint4 part[NFIN * NMLP * 8];
};
__device__ __align__(1024) Scratch g_scratch;

__device__ __forceinline__ void mbar_init(uint32_t bar, uint32_t cnt) {
    asm volatile("mbarrier.init.shared::cta.b64 [%0], %1;" ::"r"(bar), "r"(cnt) : "memory");
}
__device__ __forceinline__ void mbar_expect_tx(uint32_t bar, uint32_t bytes) {
    asm volatile("mbarrier.arrive.expect_tx.shared::cta.b64 _, [%0], %1;" ::"r"(bar), "r"(bytes) : "memory");
}
__device__ __forceinline__ void mbar_arrive(uint32_t bar) {
    asm volatile("mbarrier.arrive.shared::cta.b64 _, [%0];" ::"r"(bar) : "memory");
}
__device__ __forceinline__ bool mbar_test(uint32_t bar, uint32_t parity) {
    uint32_t ok;
    asm volatile("{\n.reg .pred p;\nmbarrier.test_wait.parity.shared::cta.b64 p, [%1], %2;\nselp.u32 %0, 1, 0, p;\n}"
                 : "=r"(ok) : "r"(bar), "r"(parity) : "memory");
    return ok;
}
__device__ __forceinline__ bool mbar_try(uint32_t bar, uint32_t parity) {
    uint32_t ok;
    asm volatile("{\n.reg .pred p;\nmbarrier.try_wait.parity.shared::cta.b64 p, [%1], %2;\nselp.u32 %0, 1, 0, p;\n}"
                 : "=r"(ok) : "r"(bar), "r"(parity) : "memory");
    return ok;
}
constexpr int SPIN_LIMIT = 1 << 20;
__device__ __forceinline__ void mbar_wait(uint32_t bar, uint32_t parity) {
    int n = 0;
    while (!mbar_try(bar, parity)) { if (++n > SPIN_LIMIT) __trap(); }
}
__device__ __forceinline__ void bulk_load(uint32_t dst, const void* src, uint32_t bytes, uint32_t bar) {
    asm volatile("cp.async.bulk.shared::cluster.global.mbarrier::complete_tx::bytes [%0], [%1], %2, [%3];"
                 ::"r"(dst), "l"(src), "r"(bytes), "r"(bar) : "memory");
}
__device__ __forceinline__ void tma2d(uint32_t dst, const CUtensorMap* tm, int c0, int c1, uint32_t bar) {
    asm volatile("cp.async.bulk.tensor.2d.shared::cluster.global.mbarrier::complete_tx::bytes [%0], [%1, {%3, %4}], [%2];"
                 ::"r"(dst), "l"(tm), "r"(bar), "r"(c0), "r"(c1) : "memory");
}
__device__ __forceinline__ void bulk_load_stream(uint32_t dst, const void* src, uint32_t bytes, uint32_t bar, uint64_t pol) {
    asm volatile("cp.async.bulk.shared::cluster.global.mbarrier::complete_tx::bytes.L2::cache_hint [%0], [%1], %2, [%3], %4;"
                 ::"r"(dst), "l"(src), "r"(bytes), "r"(bar), "l"(pol) : "memory");
}
__device__ __forceinline__ void tma2d_stream(uint32_t dst, const CUtensorMap* tm, int c0, int c1, uint32_t bar, uint64_t pol) {
    asm volatile("cp.async.bulk.tensor.2d.shared::cluster.global.mbarrier::complete_tx::bytes.L2::cache_hint [%0], [%1, {%3, %4}], [%2], %5;"
                 ::"r"(dst), "l"(tm), "r"(bar), "r"(c0), "r"(c1), "l"(pol) : "memory");
}
__device__ __forceinline__ bool elect_one() {
    uint32_t p;
    asm volatile("{\n.reg .pred p;\nelect.sync _|p, 0xffffffff;\nselp.u32 %0, 1, 0, p;\n}" : "=r"(p));
    return p;
}
__device__ __forceinline__ void cons_sync() { asm volatile("bar.sync 1, 256;" ::: "memory"); }

__device__ __forceinline__ uint32_t mapa(uint32_t addr, uint32_t rank) {
    uint32_t r;
    asm("mapa.shared::cluster.u32 %0, %1, %2;" : "=r"(r) : "r"(addr), "r"(rank));
    return r;
}
__device__ __forceinline__ void st_async_b32(uint32_t addr, uint32_t v, uint32_t bar) {
    asm volatile("st.async.weak.shared::cluster.mbarrier::complete_tx::bytes.b32 [%0], %1, [%2];" ::"r"(addr), "r"(v), "r"(bar) : "memory");
}
__device__ __forceinline__ void st_async_v2(uint32_t addr, uint32_t v0, uint32_t v1, uint32_t bar) {
    asm volatile("st.async.weak.shared::cluster.mbarrier::complete_tx::bytes.v2.b32 [%0], {%1, %2}, [%3];" ::"r"(addr), "r"(v0), "r"(v1), "r"(bar) : "memory");
}

__device__ __forceinline__ void mma_bf16(float (&d)[4], uint32_t a0, uint32_t a1, uint32_t a2, uint32_t a3, uint32_t b0, uint32_t b1) {
    asm volatile("mma.sync.aligned.m16n8k16.row.col.f32.bf16.bf16.f32 {%0,%1,%2,%3}, {%4,%5,%6,%7}, {%8,%9}, {%0,%1,%2,%3};"
                 : "+f"(d[0]), "+f"(d[1]), "+f"(d[2]), "+f"(d[3])
                 : "r"(a0), "r"(a1), "r"(a2), "r"(a3), "r"(b0), "r"(b1));
}
__device__ __forceinline__ void ldsm4(uint32_t (&r)[4], uint32_t addr) {
    asm volatile("ldmatrix.sync.aligned.m8n8.x4.shared.b16 {%0,%1,%2,%3}, [%4];"
                 : "=r"(r[0]), "=r"(r[1]), "=r"(r[2]), "=r"(r[3]) : "r"(addr) : "memory");
}
__device__ __forceinline__ void ldsm4t(uint32_t (&r)[4], uint32_t addr) {
    asm volatile("ldmatrix.sync.aligned.m8n8.x4.trans.shared.b16 {%0,%1,%2,%3}, [%4];"
                 : "=r"(r[0]), "=r"(r[1]), "=r"(r[2]), "=r"(r[3]) : "r"(addr) : "memory");
}
__device__ __forceinline__ uint4 lds128(uint32_t a) {
    uint4 v;
    asm volatile("ld.shared.v4.u32 {%0,%1,%2,%3}, [%4];" : "=r"(v.x), "=r"(v.y), "=r"(v.z), "=r"(v.w) : "r"(a) : "memory");
    return v;
}
__device__ __forceinline__ uint2 lds64(uint32_t a) {
    uint2 v;
    asm volatile("ld.shared.v2.u32 {%0,%1}, [%2];" : "=r"(v.x), "=r"(v.y) : "r"(a) : "memory");
    return v;
}
__device__ __forceinline__ uint32_t lds32(uint32_t a) {
    uint32_t v;
    asm volatile("ld.shared.u32 %0, [%1];" : "=r"(v) : "r"(a) : "memory");
    return v;
}
__device__ __forceinline__ void sts128(uint32_t a, uint4 v) {
    asm volatile("st.shared.v4.u32 [%0], {%1,%2,%3,%4};" ::"r"(a), "r"(v.x), "r"(v.y), "r"(v.z), "r"(v.w) : "memory");
}
__device__ __forceinline__ void sts32(uint32_t a, uint32_t v) {
    asm volatile("st.shared.u32 [%0], %1;" ::"r"(a), "r"(v) : "memory");
}
__device__ __forceinline__ void sts16(uint32_t a, uint16_t v) {
    asm volatile("st.shared.u16 [%0], %1;" ::"r"(a), "h"(v) : "memory");
}
__device__ __forceinline__ float bf_lo(uint32_t v) { return __uint_as_float(v << 16); }
__device__ __forceinline__ float bf_hi(uint32_t v) { return __uint_as_float(v & 0xffff0000u); }
__device__ __forceinline__ uint32_t pack_bf(float lo, float hi) {
    uint32_t r;
    asm("cvt.rn.bf16x2.f32 %0, %1, %2;" : "=r"(r) : "f"(hi), "f"(lo));
    return r;
}
__device__ __forceinline__ float rnd_bf(float v) { return bf_lo(pack_bf(v, 0.f)); }

__device__ __forceinline__ unsigned long long fx_encode(float v) {
    return ((unsigned long long)__float2ll_rn(v * FX_SCALE) << 8) + 1ull;
}
__device__ __forceinline__ float fx_decode(uint32_t lo, uint32_t hi) {
    return fmaf(__int2float_rn((int)hi), 1.0f / 64.0f, __uint2float_rn(lo & 0xffffff00u) * (FX_INV / 256.0f));
}
__device__ __forceinline__ uint32_t gtime32() {
    uint32_t t;
    asm volatile("mov.u32 %0, %%globaltimer_lo;" : "=r"(t));
    return t;
}
__device__ __forceinline__ void wait_until(uint32_t t0, uint32_t ns) {
    for (int n = 0; gtime32() - t0 < ns && n < SPIN_LIMIT; n++) {}
}
__device__ __forceinline__ void spin_cycles(uint32_t n) {
    uint32_t t0, t;
    asm volatile("mov.u32 %0, %%clock;" : "=r"(t0));
    do { asm volatile("mov.u32 %0, %%clock;" : "=r"(t)); } while (t - t0 < n);
}
__device__ __forceinline__ void red_add64(unsigned long long* p, unsigned long long v) {
    asm volatile("red.relaxed.gpu.global.add.u64 [%0], %1;" ::"l"(p), "l"(v) : "memory");
}
__device__ __forceinline__ void ld_relaxed2x64(uint4& v, const void* p) {
    asm volatile("{\n.reg .b64 a, b;\nld.relaxed.gpu.global.v2.b64 {a, b}, [%4];\nmov.b64 {%0, %1}, a;\nmov.b64 {%2, %3}, b;\n}"
                 : "=r"(v.x), "=r"(v.y), "=r"(v.z), "=r"(v.w) : "l"(p) : "memory");
}
__device__ __forceinline__ void ld_relaxed128(uint4& v, const uint4* p) {
    asm volatile("ld.relaxed.gpu.global.v4.u32 {%0,%1,%2,%3}, [%4];" : "=r"(v.x), "=r"(v.y), "=r"(v.z), "=r"(v.w) : "l"(p) : "memory");
}
__device__ __forceinline__ uint32_t and3(uint32_t a, uint32_t b, uint32_t c) {
    uint32_t r;
    asm("lop3.b32 %0, %1, %2, %3, 0x80;" : "=r"(r) : "r"(a), "r"(b), "r"(c));
    return r;
}
__device__ __forceinline__ bool all_marked(const uint4& a, const uint4& b) {
    return __all_sync(~0u, and3(and3(a.x, a.y, a.z), and3(a.w, b.x, b.y), and3(b.z, b.w, 1u)));
}
__device__ __forceinline__ bool all_complete(const uint4& a, const uint4& b) {
    return __all_sync(~0u, and3(and3(a.x, a.z, b.x), b.z, 32u));
}
__device__ __forceinline__ float bf16_at(uint32_t a) {
    uint16_t v;
    asm volatile("ld.shared.u16 %0, [%1];" : "=h"(v) : "r"(a) : "memory");
    return __uint_as_float((uint32_t)v << 16);
}

__device__ __forceinline__ int bpos(int k) { return ((k >> 1) & 3) * 16 + ((k >> 4) & 3) * 4 + ((k >> 3) & 1) * 2 + (k & 1); }

__device__ __forceinline__ void gemv1_partial(const uint32_t* a1, uint32_t hb0, uint32_t hb1, int j, int c, uint32_t a) {
    float t0[4] = {0.f, 0.f, 0.f, 0.f}, t1[4] = {0.f, 0.f, 0.f, 0.f}, t2[4] = {0.f, 0.f, 0.f, 0.f}, t3[4] = {0.f, 0.f, 0.f, 0.f};
#pragma unroll
    for (int k = 0; k < 2; k++) {
        const uint32_t m0 = (j == k) ? hb0 : 0u, m1 = (j == k) ? hb1 : 0u;
        const uint32_t n0 = (j == k + 2) ? hb0 : 0u, n1 = (j == k + 2) ? hb1 : 0u;
        mma_bf16(t0, a1[8 * k], a1[8 * k + 1], a1[8 * k + 2], a1[8 * k + 3], m0, m1);
        mma_bf16(t1, a1[8 * k + 4], a1[8 * k + 5], a1[8 * k + 6], a1[8 * k + 7], m0, m1);
        mma_bf16(t2, a1[8 * k + 16], a1[8 * k + 17], a1[8 * k + 18], a1[8 * k + 19], n0, n1);
        mma_bf16(t3, a1[8 * k + 20], a1[8 * k + 21], a1[8 * k + 22], a1[8 * k + 23], n0, n1);
    }
    const bool up2 = c & 2, up1 = c & 1;
    float r4[4], r2[2];
    const float send[4] = {up2 ? t2[0] : t0[1], up2 ? t2[2] : t0[3], up2 ? t3[0] : t1[1], up2 ? t3[2] : t1[3]};
    const float keep[4] = {up2 ? t2[1] : t0[0], up2 ? t2[3] : t0[2], up2 ? t3[1] : t1[0], up2 ? t3[3] : t1[2]};
#pragma unroll
    for (int i = 0; i < 4; i++) r4[i] = keep[i] + __shfl_xor_sync(~0u, send[i], 2);
#pragma unroll
    for (int i = 0; i < 2; i++) r2[i] = (up1 ? r4[i + 2] : r4[i]) + __shfl_xor_sync(~0u, up1 ? r4[i] : r4[i + 2], 1);
    sts32(a, __float_as_uint(r2[0]));
    sts32(a + 32, __float_as_uint(r2[1]));
}

__device__ __forceinline__ float sum8(uint32_t a) {
    float p[8];
#pragma unroll
    for (int w = 0; w < 8; w++) p[w] = __uint_as_float(lds32(a + w * 256));
    return ((p[0] + p[1]) + (p[2] + p[3])) + ((p[4] + p[5]) + (p[6] + p[7]));
}

struct Maps { CUtensorMap v, wq, wo, w1, w2; };

__global__ void __cluster_dims__(2, 1, 1) __launch_bounds__(NTHREADS, 1)
decode_block_kernel(const __grid_constant__ Maps tm,
                    const __nv_bfloat16* __restrict__ x, const __nv_bfloat16* __restrict__ Kc,
                    const __nv_bfloat16* __restrict__ b1, const __nv_bfloat16* __restrict__ b2,
                    __nv_bfloat16* __restrict__ out, Scratch* __restrict__ scr, uint32_t tile_ns_x16) {
    unsigned long long* const g_acc1 = scr->acc1;
    unsigned int* const g_tick = scr->tick;
    uint4* const g_part = scr->part;
    extern __shared__ unsigned char smem_raw[];
    const uint32_t sb = ((uint32_t)__cvta_generic_to_shared(smem_raw) + 1023u) & ~1023u;
    const uint32_t bar_full = sb + OFF_BAR, bar_empty = bar_full + NST * 8;
    const uint32_t bar_q = bar_empty + NST * 8, bar_ml = bar_q + 8, bar_o = bar_ml + 8, bar_end = bar_o + 8, bar_go = bar_end + 8;

    const char* ksrc = (const char*)Kc + (size_t)blockIdx.x * (KEYS_PER_CTA * DH * 2);
    constexpr uint64_t pol = 0x12F0000000000000ull;
    if ((threadIdx.x & ~32) == 0) {
        const int k = threadIdx.x >> 5;
        mbar_init(bar_full + (T_K0 + k) * 8, 1);
        asm volatile("fence.mbarrier_init.release.cluster;" ::: "memory");
        mbar_expect_tx(bar_full + (T_K0 + k) * 8, TILE_BYTES);
        bulk_load_stream(sb + OFF_RING + (T_K0 + k) * TILE_BYTES, ksrc + k * TILE_BYTES, TILE_BYTES, bar_full + (T_K0 + k) * 8, pol);
    }
    int tid = threadIdx.x;
    asm volatile("" : "+r"(tid));
    const int lane = tid & 31;
    const int warp = __shfl_sync(~0u, tid >> 5, 0);
    const int bh = blockIdx.x >> 1, rank = blockIdx.x & 1;
    const int b = bh >> 5, h = bh & 31;
    const bool is_mlp = (rank == 0) && (bh < NMLP);
    const int f0 = bh * 32;

    if (elect_one()) {
        if (warp < 6) {
            if (warp >= 2) {
                const int s = T_WQ + warp - 2;
                mbar_init(bar_full + s * 8, 1);
                asm volatile("fence.mbarrier_init.release.cluster;" ::: "memory");
                mbar_expect_tx(bar_full + s * 8, TILE_BYTES);
                tma2d(sb + OFF_RING + s * TILE_BYTES, &tm.wq, h * DH + rank * 64, s * 128, bar_full + s * 8);
            }
        } else if (warp == 7) {
#pragma unroll
            for (int s = 0; s < NST; s++) mbar_init(bar_empty + s * 8, 8);
            asm volatile("fence.mbarrier_init.release.cluster;" ::: "memory");
        } else if (warp == 8) {
#pragma unroll
            for (int s = T_K0 + 2; s < NST; s++) mbar_init(bar_full + s * 8, 1);
            asm volatile("fence.mbarrier_init.release.cluster;" ::: "memory");
#pragma unroll
            for (int s = T_K0 + 2; s < T_K0 + NINIT; s++) {
                mbar_expect_tx(bar_full + s * 8, TILE_BYTES);
                bulk_load_stream(sb + OFF_RING + s * TILE_BYTES, ksrc + (size_t)(s - T_K0) * TILE_BYTES, TILE_BYTES, bar_full + s * 8, pol);
            }
        } else if (warp == 9) {
            mbar_init(bar_q, 2); mbar_init(bar_ml, 1); mbar_init(bar_o, 2); mbar_init(bar_end, 1); mbar_init(bar_go, 1);
            asm volatile("fence.mbarrier_init.release.cluster;" ::: "memory");
            mbar_expect_tx(bar_q, 128);
            mbar_expect_tx(bar_ml, is_mlp ? 8 + 2048 + 1024 + 64 : 8);
            if (is_mlp) {
                bulk_load(sb + OFF_X, x, 2048, bar_ml);
                bulk_load(sb + OFF_X + 2048, b2, 1024, bar_ml);
                bulk_load(sb + OFF_X + 3072, b1 + f0, 64, bar_ml);
            }
            mbar_expect_tx(bar_o, 512);
            asm volatile("prefetch.tensormap [%0];" ::"l"(&tm.wo) : "memory");
            asm volatile("prefetch.tensormap [%0];" ::"l"(&tm.v) : "memory");
            asm volatile("prefetch.tensormap [%0];" ::"l"(&tm.w1) : "memory");
            asm volatile("prefetch.tensormap [%0];" ::"l"(&tm.w2) : "memory");
        }
    }
    __syncwarp();
    asm volatile("barrier.cluster.arrive.relaxed.aligned;" ::: "memory");

    if (warp == 8) {
        const uint32_t t_start = gtime32();
        asm volatile("barrier.cluster.wait.aligned;" ::: "memory");
        if (lane == 0) {
#pragma unroll
            for (int w = 0; w < 4; w++) mbar_wait(bar_full + (T_WQ + w) * 8, 0);
#pragma unroll
            for (int k = NINIT; k < KPRE; k++) {
                const uint32_t fb = bar_full + (T_K0 + k) * 8;
                mbar_expect_tx(fb, TILE_BYTES);
                bulk_load_stream(sb + OFF_RING + (T_K0 + k) * TILE_BYTES, ksrc + (size_t)k * TILE_BYTES, TILE_BYTES, fb, pol);
            }
            const int vline0 = (bh * SK + rank * KEYS_PER_CTA) * 2;
            const int tend = is_mlp ? T_END : T_W1;
            const int lead16 = LEAD * 16 + (bh < NMLP ? SKEW : -2 * SKEW);
            int st = 0, ph = 0;
#pragma unroll 1
            for (int t = NST; t < tend; t++) {
                const uint32_t dst = sb + OFF_RING + st * TILE_BYTES, fb = bar_full + st * 8;
                mbar_wait(bar_empty + st * 8, ph);
                wait_until(t_start, ((t * 16 - lead16) * tile_ns_x16) >> 8);
                if (t == T_W1) {
                    mbar_wait(bar_full + ((T_W1 - 1 - WLATE) % NST) * 8, ((T_W1 - 1 - WLATE) / NST) & 1);
                }
                mbar_expect_tx(fb, TILE_BYTES);
                if (t < T_K1) {
                    tma2d(dst, &tm.wo, rank * 256 + (t - T_WO) * 64, h * DH, fb);
                } else if (t < T_V) {
                    bulk_load_stream(dst, ksrc + (size_t)(t - 8) * TILE_BYTES, TILE_BYTES, fb, pol);
                } else if (t < T_W1) {
                    tma2d_stream(dst, &tm.v, 0, vline0 + (t - T_V) * (TILE_KEYS * 2), fb, pol);
                } else if (t < T_W2) {
                    tma2d(dst, &tm.w1, f0, (t - T_W1) * 256, fb);
                } else {
#pragma unroll
                    for (int i = 0; i < 4; i++) tma2d(dst + i * 4096, &tm.w2, ((t - T_W2) * 4 + i) * 64, f0, fb);
                }
                if (++st == NST) { st = 0; ph ^= 1; }
            }
        }
        if (is_mlp) {
            __syncwarp();
            const int rr = lane & 7, mi = lane >> 3;
            float cs[4][4];
#pragma unroll
            for (int i = 0; i < 4; i++) cs[i][0] = cs[i][1] = cs[i][2] = cs[i][3] = 0.f;
#pragma unroll
            for (int t = 0; t < 2; t++) {
                const uint32_t a = sb + OFF_RING + (T_W1 % NST + t) * TILE_BYTES + ((mi >> 1) * 8 + rr) * 64 + ((mi & 1) ^ (rr >> 1)) * 16;
                mbar_wait(bar_full + (T_W1 % NST + t) * 8, (T_W1 / NST) & 1);
#pragma unroll 4
                for (int k = 0; k < 16; k += 2) {
                    uint32_t w[4][4];
                    ldsm4t(w[0], a + k * 1024); ldsm4t(w[1], (a ^ 32) + k * 1024);
                    ldsm4t(w[2], a + k * 1024 + 1024); ldsm4t(w[3], (a ^ 32) + k * 1024 + 1024);
#pragma unroll
                    for (int i = 0; i < 4; i++) mma_bf16(cs[i], w[i][0], w[i][1], w[i][2], w[i][3], 0x3f803f80u, 0x3f803f80u);
                }
            }
            const int c = lane & 3;
            const float lo = (c & 1) ? cs[0][2] + cs[2][2] : cs[0][0] + cs[2][0], hi = (c & 1) ? cs[1][2] + cs[3][2] : cs[1][0] + cs[3][0];
            sts32(sb + OFF_CS + (c * 8 + (lane >> 2)) * 4, __float_as_uint((c & 2) ? hi : lo));
            asm volatile("bar.arrive 2, 288;" ::: "memory");
        }
        return;
    }

    if (warp == 9) {
        if (is_mlp) {
#pragma unroll
            for (int i = 0; i < 8; i++) g_part[((i * 4 + (lane >> 3)) * NMLP + bh) * 8 + (lane & 7)] = make_uint4(0, 0, 0, 0);
            __threadfence();
        }
        asm volatile("barrier.cluster.wait.aligned;" ::: "memory");
        if (lane == 0) mbar_arrive(bar_o);
        if (is_mlp) {
            mbar_wait(bar_end, 0);
            for (int n = 0;; n++) {
                unsigned v = 0;
                if (lane < 8) asm volatile("ld.relaxed.gpu.global.u32 %0, [%1];" : "=r"(v) : "l"(g_tick + lane * 32) : "memory");
                if (__reduce_add_sync(~0u, v) >= NCTA) break;
                if (n > SPIN_LIMIT) __trap();
            }
            if (lane == 0) mbar_arrive(bar_go);
        }
        return;
    }

    const int g = lane >> 2, c = lane & 3;
    const int rr = lane & 7, mi = lane >> 3;
    const int mb_ = g & 1, j4 = g >> 1;
    const int d0 = warp * 64 + j4 * 16 + c * 2;
    uint32_t qa[16], wf[64];
    {
        if (warp == 6) {
            const uint4 xa0 = __ldg((const uint4*)(x + b * D_MODEL) + lane), xa1 = __ldg((const uint4*)(x + b * D_MODEL) + 32 + lane);
            const uint32_t xa[8] = {xa0.x, xa0.y, xa0.z, xa0.w, xa1.x, xa1.y, xa1.z, xa1.w};
            float s = 0.f;
#pragma unroll
            for (int i = 0; i < 8; i++) s += bf_lo(xa[i]) + bf_hi(xa[i]);
#pragma unroll
            for (int o = 16; o; o >>= 1) s += __shfl_xor_sync(~0u, s, o);
            const float mean = s * (1.0f / D_MODEL);
            float v = 0.f;
#pragma unroll
            for (int i = 0; i < 8; i++) { const float e0 = bf_lo(xa[i]) - mean, e1 = bf_hi(xa[i]) - mean; v += e0 * e0 + e1 * e1; }
#pragma unroll
            for (int o = 16; o; o >>= 1) v += __shfl_xor_sync(~0u, v, o);
            const float mb = rnd_bf(mean);
            const float den = rnd_bf(sqrtf(rnd_bf(rnd_bf(v * (1.0f / D_MODEL)) + 1e-5f)));
#pragma unroll
            for (int i = 0; i < 8; i++) {
                const int k = (i >> 2) * 256 + lane * 8 + (i & 3) * 2;
                sts32(sb + OFF_XN + ((k & ~63) + bpos(k)) * 2,
                      pack_bf(__fdiv_rn(rnd_bf(bf_lo(xa[i]) - mb), den), __fdiv_rn(rnd_bf(bf_hi(xa[i]) - mb), den)));
            }
        }
        asm volatile("barrier.cluster.wait.aligned;" ::: "memory");
        cons_sync();

        float q0[4] = {0.f, 0.f, 0.f, 0.f}, q1[4] = {0.f, 0.f, 0.f, 0.f};
        const uint32_t aoff = ((warp >> 2) * 64 + (mi >> 1) * 8 + rr) * 128 + (((warp & 3) * 2 + (mi & 1)) ^ rr) * 16;
#pragma unroll
        for (int t = 0; t < 4; t++) {
            const uint32_t xaddr = sb + OFF_XN + (t * 2 + (warp >> 2)) * 128 + c * 32;
            const uint4 p0 = lds128(xaddr), p1 = lds128(xaddr + 16);
            const uint32_t base = sb + OFF_RING + (T_WQ + t) * TILE_BYTES + aoff;
            mbar_wait(bar_full + (T_WQ + t) * 8, 0);
            uint32_t a0[4], a1[4], a2[4], a3[4];
            ldsm4t(a0, base); ldsm4t(a1, base + 2048); ldsm4t(a2, base + 4096); ldsm4t(a3, base + 6144);
            mma_bf16(q0, a0[0], a0[1], a0[2], a0[3], p0.x, p0.y);
            mma_bf16(q1, a1[0], a1[1], a1[2], a1[3], p0.z, p0.w);
            mma_bf16(q0, a2[0], a2[1], a2[2], a2[3], p1.x, p1.y);
            mma_bf16(q1, a3[0], a3[1], a3[2], a3[3], p1.z, p1.w);
            __syncwarp();
            if (lane == 0) mbar_arrive(bar_empty + (T_WQ + t) * 8);
        }
        if (c < 2) sts32(sb + OFF_PART + (warp * 16 + c * 8 + g) * 4, __float_as_uint(c ? q0[2] + q1[2] : q0[0] + q1[0]));
        cons_sync();
        if (warp == 0) {
            const uint2 u = lds64(sb + OFF_PART + lane * 8), w = lds64(sb + OFF_PART + 256 + lane * 8);
            const uint32_t qq = pack_bf(__uint_as_float(u.x) + __uint_as_float(w.x), __uint_as_float(u.y) + __uint_as_float(w.y));
            const uint32_t dst = sb + OFF_Q + rank * 128 + lane * 4;
            sts32(dst, qq);
            st_async_b32(mapa(dst, rank ^ 1), qq, mapa(bar_q, rank ^ 1));
            __syncwarp();
            if (lane == 0) mbar_arrive(bar_q);
        }
        mbar_wait(bar_q, 0);
#pragma unroll
        for (int j = 0; j < 16; j++) qa[j] = lds32(sb + OFF_Q + ((j & 8) + ((g + j) & 7)) * 16 + c * 4);
    }

    int st = T_K0, ph = 0;
    float mx = -INFINITY;
    {
        uint32_t koff0 = sb + OFF_RING + (warp * 8 + rr) * 256 + ((rr + mi) & 7) * 16;
        uint32_t koff1 = sb + OFF_RING + (warp * 8 + rr) * 256 + ((rr + mi + 4) & 7) * 16;
        asm volatile("" : "+r"(koff0), "+r"(koff1));
        const bool valid = (c == (g >> 1));
        uint32_t spos = sb + OFF_SP + bpos(warp * 8 + g) * 2;
        auto k_tiles = [&](int n) {
#pragma unroll 1
            for (int i = 0; i < n; i++) {
                const uint32_t base = st * TILE_BYTES;
                mbar_wait(bar_full + st * 8, ph);
                uint32_t k0[4], k1[4], k2[4], k3[4];
                ldsm4(k0, base + koff0); ldsm4(k1, base + koff1);
                ldsm4(k2, base + koff0 + 128); ldsm4(k3, base + koff1 + 128);
                float s0[4] = {0.f, 0.f, 0.f, 0.f}, s1[4] = {0.f, 0.f, 0.f, 0.f};
                mma_bf16(s0, qa[0], qa[2], qa[1], qa[3], k0[0], k0[1]);
                mma_bf16(s1, qa[0], qa[2], qa[1], qa[3], k0[2], k0[3]);
                mma_bf16(s0, qa[4], qa[6], qa[5], qa[7], k1[0], k1[1]);
                mma_bf16(s1, qa[4], qa[6], qa[5], qa[7], k1[2], k1[3]);
                mma_bf16(s0, qa[8], qa[10], qa[9], qa[11], k2[0], k2[1]);
                mma_bf16(s1, qa[8], qa[10], qa[9], qa[11], k2[2], k2[3]);
                mma_bf16(s0, qa[12], qa[14], qa[13], qa[15], k3[0], k3[1]);
                mma_bf16(s1, qa[12], qa[14], qa[13], qa[15], k3[2], k3[3]);
                __syncwarp();
                if (lane == 0) mbar_arrive(bar_empty + st * 8);
                const float raw = (g & 1) ? s0[1] + s1[3] : s0[0] + s1[2];
                const uint32_t sc = pack_bf(rnd_bf(raw) * 0.08838834764831845f, 0.f);
                if (valid) { sts16(spos, (uint16_t)sc); mx = fmaxf(mx, bf_lo(sc)); }
                spos += TILE_KEYS * 2;
                if (++st == NST) { st = 0; ph ^= 1; }
            }
        };
        k_tiles(KPRE);
        {
            static_assert(T_WO == NST, "wo tiles sit in slots 0..3, second pass");
            const int s = warp >> 1;
            const int row = (mi >> 1) * 4 + (rr >> 1) + (rr & 1) * 8;
            const uint32_t base = sb + OFF_RING + s * TILE_BYTES + row * 128;
            const uint32_t c0 = (((mi & 1) * 2 + (warp & 1)) ^ (row & 7)) * 16, c1 = c0 ^ 64;
            mbar_wait(bar_full + s * 8, 1);
#pragma unroll
            for (int t = 0; t < 8; t++) {
                ldsm4t(*(uint32_t(*)[4])(wf + 8 * t), base + t * 2048 + c0);
                ldsm4t(*(uint32_t(*)[4])(wf + 8 * t + 4), base + t * 2048 + c1);
            }
            __syncwarp();
            if (lane < 4) mbar_arrive(bar_empty + lane * 8);
            st = 4;
        }
        k_tiles(NTILE - KPRE);
    }
    {
#pragma unroll
        for (int o = 16; o; o >>= 1) mx = fmaxf(mx, __shfl_xor_sync(~0u, mx, o));
        if (lane == 0) sts32(sb + OFF_RED + warp * 4, __float_as_uint(mx));
        cons_sync();
        const uint4 m0 = lds128(sb + OFF_RED), m1 = lds128(sb + OFF_RED + 16);
        const float mloc = fmaxf(fmaxf(fmaxf(__uint_as_float(m0.x), __uint_as_float(m0.y)), fmaxf(__uint_as_float(m0.z), __uint_as_float(m0.w))),
                                 fmaxf(fmaxf(__uint_as_float(m1.x), __uint_as_float(m1.y)), fmaxf(__uint_as_float(m1.z), __uint_as_float(m1.w))));
        const uint4 s0 = lds128(sb + OFF_SP + tid * 16), s1 = lds128(sb + OFF_SP + 4096 + tid * 16);
        const uint32_t sv[8] = {s0.x, s0.y, s0.z, s0.w, s1.x, s1.y, s1.z, s1.w};
        constexpr float LOG2E = 1.4426950408889634f;
        float l = 0.f;
#pragma unroll
        for (int i = 0; i < 8; i++) l += exp2f((bf_lo(sv[i]) - mloc) * LOG2E) + exp2f((bf_hi(sv[i]) - mloc) * LOG2E);
#pragma unroll
        for (int o = 16; o; o >>= 1) l += __shfl_xor_sync(~0u, l, o);
        if (lane == 0) sts32(sb + OFF_RED + 32 + warp * 4, __float_as_uint(l));
        cons_sync();
        const uint4 l0 = lds128(sb + OFF_RED + 32), l1 = lds128(sb + OFF_RED + 48);
        const float lloc = ((__uint_as_float(l0.x) + __uint_as_float(l0.y)) + (__uint_as_float(l0.z) + __uint_as_float(l0.w))) +
                           ((__uint_as_float(l1.x) + __uint_as_float(l1.y)) + (__uint_as_float(l1.z) + __uint_as_float(l1.w)));
        if (tid == 0) st_async_v2(mapa(sb + OFF_ML, rank ^ 1), __float_as_uint(mloc), __float_as_uint(lloc), mapa(bar_ml, rank ^ 1));
        mbar_wait(bar_ml, 0);
        const uint2 pml = lds64(sb + OFF_ML);
        const float mp = __uint_as_float(pml.x), lp = __uint_as_float(pml.y);
        const float M = fmaxf(mloc, mp);
        const float m_a = rank ? mp : mloc, l_a = rank ? lp : lloc, m_b = rank ? mloc : mp, l_b = rank ? lloc : lp;
        const float L = l_a * exp2f((m_a - M) * LOG2E) + l_b * exp2f((m_b - M) * LOG2E);
        const float inv = 1.0f / L;
        uint32_t pv[8];
#pragma unroll
        for (int i = 0; i < 8; i++)
            pv[i] = pack_bf(exp2f((bf_lo(sv[i]) - M) * LOG2E) * inv, exp2f((bf_hi(sv[i]) - M) * LOG2E) * inv);
        sts128(sb + OFF_SP + tid * 16, make_uint4(pv[0], pv[1], pv[2], pv[3]));
        sts128(sb + OFF_SP + 4096 + tid * 16, make_uint4(pv[4], pv[5], pv[6], pv[7]));
        cons_sync();
    }
    unsigned long long* acc1_dst = g_acc1 + b * D_MODEL + rank * 256 + warp * 32 + c * 8 + g;
    uint32_t o_peer = sb + OFF_OP + (warp * 8 + g) * 8;
    uint32_t o_dst = mapa(o_peer, rank ^ 1), o_bar = mapa(bar_o, rank ^ 1);
    uint32_t o_loc = sb + OFF_O + (warp * 8 + g) * 4, o_src = sb + OFF_O + mi * 16;
    unsigned* tick_dst = g_tick + (bh & 7) * 32;
    asm volatile("" : "+l"(acc1_dst), "+l"(tick_dst), "+r"(o_peer), "+r"(o_dst), "+r"(o_bar), "+r"(o_loc), "+r"(o_src));
    const bool is_fin = bh < NFIN;
    const unsigned long long* p1 = g_acc1 + mb_ * D_MODEL + warp * 64 + j4 * 8 + c * 2;
    uint4* part_dst = g_part + ((warp * 4 + c) * NMLP + bh) * 8 + g;
    const uint4* inbox = g_part + bh * (NMLP * 8) + tid;
    const uint4* inbox2 = tid < (NMLP - 32) * 8 ? inbox + 256 : inbox;
    float wsel = tid < (NMLP - 32) * 8 ? 1.0f : 0.0f;
    __nv_bfloat16* out_dst = out + ((lane >> 3) & 1) * D_MODEL + bh * 16 + (lane >> 4) * 8 + (lane & 7);
    asm volatile("" : "+l"(p1), "+l"(part_dst), "+l"(inbox), "+l"(inbox2), "+f"(wsel), "+l"(out_dst));
    uint32_t xv[2] = {lds32(sb + OFF_X + (mb_ * D_MODEL + d0) * 2), lds32(sb + OFF_X + (mb_ * D_MODEL + d0 + 8) * 2)};
    float b1v = bf16_at(sb + OFF_X + 3072 + lane * 2);
    float b2v = bf16_at(sb + OFF_X + 2048 + ((bh & 31) * 16 + (lane >> 4) * 8 + (lane & 7)) * 2);
    uint32_t a_part = sb + OFF_PART + warp * 256 + ((c >> 1) * 32 + (c & 1) * 16 + g) * 4;
    uint32_t a_stat = sb + OFF_STAT + (mb_ * 16 + (c & 1) * 8 + warp) * 4;
    uint32_t a_keep = sb + OFF_RED + mb_ * 32 + c * 4;
    uint32_t a_sum = sb + OFF_PART + (warp * 32 + lane) * 4, a_cs = sb + OFF_CS + lane * 4;
    uint32_t a_hid = sb + OFF_HID + warp * 80 + lane * 2, a_hidb = sb + OFF_HID + (rr & 1) * 80 + mi * 16;
    uint32_t a_fin = sb + OFF_PART + warp * 256 + lane * 4;
    uint32_t a_hfin = sb + OFF_RED + ((lane >> 3) & 1) * 32 + ((lane >> 4) * 8 + (lane & 7)) * 2;
    int keep_h = warp * 4 + j4 == bh;
    asm volatile("" : "+r"(a_part), "+r"(a_stat), "+r"(a_keep), "+r"(a_sum), "+r"(a_cs), "+r"(a_hid), "+r"(a_hidb), "+r"(a_fin), "+r"(a_hfin),
                 "+r"(keep_h), "+f"(b1v), "+f"(b2v));
    static_assert(T_W1 % NST + 3 < NST, "w1/w2 occupy four consecutive slots with the same parity");
    constexpr int W_PAR = (T_W1 / NST) & 1;
    uint32_t w1_bar = bar_full + (T_W1 % NST + (warp >> 2)) * 8;
    uint32_t w1_a = sb + OFF_RING + (T_W1 % NST + (warp >> 2)) * TILE_BYTES + ((warp & 3) * 64 + (mi >> 1) * 8 + rr) * 64 + ((mi & 1) ^ (rr >> 1)) * 16;
    uint32_t w2_a = sb + OFF_RING + (T_W2 % NST + (warp >> 2)) * TILE_BYTES + (warp & 3) * 4096 + ((mi >> 1) * 8 + rr) * 128 + ((mi & 1) ^ rr) * 16;
    asm volatile("" : "+r"(w1_bar), "+r"(w1_a), "+r"(w2_a));
    {
        const int hh = warp >> 2, ch = 2 * (warp & 3);
        const int line = 2 * (8 * (mi >> 1) + rr) + hh;
        uint32_t voff = sb + OFF_RING + line * 128 + (((ch ^ (mi & 1) ^ (rr >> 2)) ^ (line & 7)) * 16);
        uint32_t pmask = ((c >> 1) == (g & 1)) ? 0xffffffffu : 0u;
        asm volatile("" : "+r"(voff), "+r"(pmask));
        uint32_t paddr = sb + OFF_SP + c * 32;
        float o0[4] = {0.f, 0.f, 0.f, 0.f}, o1[4] = {0.f, 0.f, 0.f, 0.f};
#pragma unroll 1
        for (int i = 0; i < NTILE; i++) {
            const uint32_t base = voff + st * TILE_BYTES;
            uint4 p0 = lds128(paddr), p1 = lds128(paddr + 16);
            p0.x &= pmask; p0.y &= pmask; p0.z &= pmask; p0.w &= pmask;
            p1.x &= pmask; p1.y &= pmask; p1.z &= pmask; p1.w &= pmask;
            asm volatile("" : "+r"(p0.x), "+r"(p0.y), "+r"(p0.z), "+r"(p0.w), "+r"(p1.x), "+r"(p1.y), "+r"(p1.z), "+r"(p1.w));
            mbar_wait(bar_full + st * 8, ph);
            uint32_t a0[4], a1[4], a2[4], a3[4];
            ldsm4t(a0, base); ldsm4t(a1, base + 4096); ldsm4t(a2, base + 8192); ldsm4t(a3, base + 12288);
            if (i == NTILE - 1 && tid == 0) {
                asm volatile("red.relaxed.gpu.global.add.u32 [%0], 1;" ::"l"(tick_dst) : "memory");
                mbar_arrive(bar_end);
            }
            mma_bf16(o0, a0[0], a0[1], a0[2], a0[3], p0.x, p0.y);
            mma_bf16(o1, a1[0], a1[1], a1[2], a1[3], p0.z, p0.w);
            mma_bf16(o0, a2[0], a2[1], a2[2], a2[3], p1.x, p1.y);
            mma_bf16(o1, a3[0], a3[1], a3[2], a3[3], p1.z, p1.w);
            __syncwarp();
            if (lane == 0) mbar_arrive(bar_empty + st * 8);
            paddr += TILE_KEYS * 2;
            if (++st == NST) { st = 0; ph ^= 1; }
        }
        const float v0 = (o0[0] + o1[0]) + (o0[3] + o1[3]);
        const float v1 = (o0[1] + o1[1]) + (o0[2] + o1[2]);
        if (c == 0) st_async_v2(o_dst, __float_as_uint(v0), __float_as_uint(v1), o_bar);
        mbar_wait(bar_o, 0);
        const uint2 pv = lds64(o_peer);
        if (c == 0) sts32(o_loc, pack_bf(v0 + __uint_as_float(pv.x), v1 + __uint_as_float(pv.y)));
        cons_sync();
    }
    {
        float d00[4] = {0.f, 0.f, 0.f, 0.f}, d01[4] = {0.f, 0.f, 0.f, 0.f}, d10[4] = {0.f, 0.f, 0.f, 0.f}, d11[4] = {0.f, 0.f, 0.f, 0.f};
        uint32_t ob[4][4];
#pragma unroll
        for (int t = 0; t < 4; t++) ldsm4(ob[t], o_src + t * 64);
#pragma unroll
        for (int t = 0; t < 4; t++) {
            mma_bf16(d00, wf[16 * t], wf[16 * t + 1], wf[16 * t + 2], wf[16 * t + 3], ob[t][0], ob[t][1]);
            mma_bf16(d10, wf[16 * t + 4], wf[16 * t + 5], wf[16 * t + 6], wf[16 * t + 7], ob[t][0], ob[t][1]);
            mma_bf16(d01, wf[16 * t + 8], wf[16 * t + 9], wf[16 * t + 10], wf[16 * t + 11], ob[t][2], ob[t][3]);
            mma_bf16(d11, wf[16 * t + 12], wf[16 * t + 13], wf[16 * t + 14], wf[16 * t + 15], ob[t][2], ob[t][3]);
        }
        const float ea = (c & 1) ? d00[2] + d01[2] : d00[0] + d01[0], eb = (c & 1) ? d10[2] + d11[2] : d10[0] + d11[0];
        const float e = (c & 2) ? eb : ea;
        red_add64(acc1_dst, fx_encode(e));
    }
    if (!is_mlp) return;

    {
        uint32_t* a1 = wf;
        uint32_t* a2 = wf + 32;
        auto load_w1 = [&]() {
#pragma unroll
            for (int k = 0; k < 4; k++) {
                ldsm4t(*(uint32_t(*)[4])(a1 + 8 * k), w1_a + k * 1024);
                ldsm4t(*(uint32_t(*)[4])(a1 + 8 * k + 4), (w1_a ^ 32) + k * 1024);
            }
        };
        auto load_w2 = [&]() {
#pragma unroll
            for (int u = 0; u < 2; u++)
#pragma unroll
                for (int T = 0; T < 4; T++) ldsm4t(*(uint32_t(*)[4])(a2 + 16 * u + 4 * T), (w2_a ^ (T * 32)) + u * 2048);
        };
        uint32_t hb0, hb1;
        int stage = 0;
        {
            uint4 ua = make_uint4(0, 0, 0, 0), ub = ua;
            int n = 0, polled = 0;
#pragma unroll 1
            do {
                if (!polled && __all_sync(~0u, mbar_test(bar_go, 0))) {
                    ld_relaxed2x64(ua, p1); ld_relaxed2x64(ub, p1 + 32);
                    polled = 1;
                }
                if (stage < 2 && __all_sync(~0u, mbar_test(w1_bar + stage * 16, W_PAR))) {
                    if (stage == 0) load_w1(); else load_w2();
                    stage++;
                }
                if (++n > SPIN_LIMIT * 16) __trap();
            } while (stage < 1 || !polled);
            if (stage < 2 && __all_sync(~0u, mbar_test(w1_bar + 16, W_PAR))) { load_w2(); stage = 2; }
            n = 0;
            while (!all_complete(ua, ub)) {
                ld_relaxed2x64(ua, p1); ld_relaxed2x64(ub, p1 + 32);
                if (++n > SPIN_LIMIT) __trap();
            }
            const uint32_t at0 = pack_bf(fx_decode(ua.x, ua.y), fx_decode(ua.z, ua.w)), at1 = pack_bf(fx_decode(ub.x, ub.y), fx_decode(ub.z, ub.w));
            hb0 = pack_bf(bf_lo(xv[0]) + bf_lo(at0), bf_hi(xv[0]) + bf_hi(at0));
            hb1 = pack_bf(bf_lo(xv[1]) + bf_lo(at1), bf_hi(xv[1]) + bf_hi(at1));
        }
        gemv1_partial(a1, hb0, hb1, j4, c, a_part);
        {
            const float h0 = bf_lo(hb0), h1 = bf_hi(hb0), h2 = bf_lo(hb1), h3 = bf_hi(hb1);
            const float s1 = (h0 + h1) + (h2 + h3);
            const float s2 = (h0 * h0 + h1 * h1) + (h2 * h2 + h3 * h3);
            float t = ((c & 1) ? s2 : s1) + __shfl_xor_sync(~0u, (c & 1) ? s1 : s2, 1);
            t += __shfl_xor_sync(~0u, t, 2);
            t += __shfl_xor_sync(~0u, t, 8);
            t += __shfl_xor_sync(~0u, t, 16);
            if ((lane & 0x1a) == 0) sts32(a_stat, __float_as_uint(t));
        }
        if (keep_h) {
            sts32(a_keep, hb0);
            sts32(a_keep + 16, hb1);
        }
        asm volatile("bar.sync 2, 288;" ::: "memory");
        if (warp < 2) {
            const uint4 q0 = lds128(sb + OFF_STAT + warp * 64), q1 = lds128(sb + OFF_STAT + warp * 64 + 16);
            const uint4 q2 = lds128(sb + OFF_STAT + warp * 64 + 32), q3 = lds128(sb + OFF_STAT + warp * 64 + 48);
            const float sacc = sum8(a_sum);
            const float cs = __uint_as_float(lds32(a_cs));
            const float mean = (((__uint_as_float(q0.x) + __uint_as_float(q0.y)) + (__uint_as_float(q0.z) + __uint_as_float(q0.w))) +
                                ((__uint_as_float(q1.x) + __uint_as_float(q1.y)) + (__uint_as_float(q1.z) + __uint_as_float(q1.w)))) * (1.0f / D_MODEL);
            const float msq = (((__uint_as_float(q2.x) + __uint_as_float(q2.y)) + (__uint_as_float(q2.z) + __uint_as_float(q2.w))) +
                               ((__uint_as_float(q3.x) + __uint_as_float(q3.y)) + (__uint_as_float(q3.z) + __uint_as_float(q3.w)))) * (1.0f / D_MODEL);
            const float var = fmaxf(msq - mean * mean, 0.f);
            float sq, iden;
            asm("sqrt.approx.ftz.f32 %0, %1;" : "=f"(sq) : "f"(rnd_bf(rnd_bf(var) + 1e-5f)));
            asm("rcp.approx.ftz.f32 %0, %1;" : "=f"(iden) : "f"(rnd_bf(sq)));
            const float z = fmaxf(rnd_bf(rnd_bf((sacc - rnd_bf(mean) * cs) * iden) + b1v), 0.f);
            sts16(a_hid, (uint16_t)pack_bf(z * z, 0.f));
        }
        if (stage < 2) { mbar_wait(w1_bar + 16, W_PAR); load_w2(); }
        cons_sync();
        uint32_t hb[4];
        ldsm4(hb, a_hidb);
        const float hfin = bf16_at(a_hfin);
        float y[4][4];
#pragma unroll
        for (int T = 0; T < 4; T++) {
            y[T][0] = y[T][1] = y[T][2] = y[T][3] = 0.f;
            mma_bf16(y[T], a2[4 * T], a2[4 * T + 1], a2[4 * T + 2], a2[4 * T + 3], hb[0], hb[1]);
        }
#pragma unroll
        for (int T = 0; T < 4; T++)
            mma_bf16(y[T], a2[16 + 4 * T], a2[16 + 4 * T + 1], a2[16 + 4 * T + 2], a2[16 + 4 * T + 3], hb[2], hb[3]);
        {
            const bool up2 = c & 2, up1 = c & 1;
            uint32_t e[4];
#pragma unroll
            for (int i = 0; i < 4; i++) e[i] = __float_as_uint(up2 ? (up1 ? y[3][i] : y[2][i]) : (up1 ? y[1][i] : y[0][i])) | 1u;
            asm volatile("st.relaxed.gpu.global.v4.u32 [%0], {%1,%2,%3,%4};" ::"l"(part_dst), "r"(e[0]), "r"(e[1]), "r"(e[2]), "r"(e[3]) : "memory");
        }
        if (!is_fin) return;
        {
            uint4 u, w;
            int n = 0;
            spin_cycles(DELAY2);
            do {
                ld_relaxed128(u, inbox); ld_relaxed128(w, inbox2);
                if (++n > SPIN_LIMIT) __trap();
            } while (!all_marked(u, w));
            const float v0 = fmaf(__uint_as_float(w.x), wsel, __uint_as_float(u.x)), v1 = fmaf(__uint_as_float(w.y), wsel, __uint_as_float(u.y));
            const float v2 = fmaf(__uint_as_float(w.z), wsel, __uint_as_float(u.z)), v3 = fmaf(__uint_as_float(w.w), wsel, __uint_as_float(u.w));
            const bool up16 = lane & 16, up8 = lane & 8;
            const float r0 = (up16 ? v2 : v0) + __shfl_xor_sync(~0u, up16 ? v0 : v2, 16);
            const float r1 = (up16 ? v3 : v1) + __shfl_xor_sync(~0u, up16 ? v1 : v3, 16);
            const float r = (up8 ? r1 : r0) + __shfl_xor_sync(~0u, up8 ? r0 : r1, 8);
            sts32(a_fin, __float_as_uint(r));
        }
        cons_sync();
        if (warp == 0) {
            const float y2 = sum8(a_sum);
            *out_dst = __ushort_as_bfloat16((unsigned short)pack_bf(hfin + rnd_bf(rnd_bf(y2) + b2v), 0.f));
        }
        if (bh == 0) {
            *(ulonglong2*)(g_acc1 + tid * 4) = make_ulonglong2(0, 0);
            *(ulonglong2*)(g_acc1 + tid * 4 + 2) = make_ulonglong2(0, 0);
            if (tid < 8) g_tick[tid * 32] = 0;
        }
    }
}

typedef CUresult (*EncodeFn)(CUtensorMap*, CUtensorMapDataType, cuuint32_t, void*, const cuuint64_t*, const cuuint64_t*,
                             const cuuint32_t*, const cuuint32_t*, CUtensorMapInterleave, CUtensorMapSwizzle,
                             CUtensorMapL2promotion, CUtensorMapFloatOOBfill);

void make_map(EncodeFn enc, CUtensorMap* tm, void* ptr, uint64_t cols, uint64_t rows, uint32_t box_cols, uint32_t box_rows,
              CUtensorMapSwizzle swz, CUtensorMapL2promotion promo = CU_TENSOR_MAP_L2_PROMOTION_NONE) {
    const cuuint64_t dims[2] = {cols, rows};
    const cuuint64_t strides[1] = {cols * 2};
    const cuuint32_t box[2] = {box_cols, box_rows};
    const cuuint32_t es[2] = {1, 1};
    enc(tm, CU_TENSOR_MAP_DATA_TYPE_BFLOAT16, 2, ptr, dims, strides, box, es, CU_TENSOR_MAP_INTERLEAVE_NONE, swz,
        promo, CU_TENSOR_MAP_FLOAT_OOB_FILL_NONE);
}

}

extern "C" void kernel_launch(void* const* d_in, const int* in_sizes, int n_in, void* d_out, int out_size) {
    (void)in_sizes; (void)n_in; (void)out_size;
    static EncodeFn enc = nullptr;
    static Scratch* scr = nullptr;
    static uint32_t tile_ns_x16 = 0;
    if (!enc) {
        void* fn = nullptr;
        cudaDriverEntryPointQueryResult qr;
        cudaGetDriverEntryPoint("cuTensorMapEncodeTiled", &fn, cudaEnableDefault, &qr);
        enc = (EncodeFn)fn;
        cudaGetSymbolAddress((void**)&scr, g_scratch);
        int dev = 0, mem_khz = 0, bus_bits = 0;
        cudaGetDevice(&dev);
        cudaDeviceGetAttribute(&mem_khz, cudaDevAttrMemoryClockRate, dev);
        cudaDeviceGetAttribute(&bus_bits, cudaDevAttrGlobalMemoryBusWidth, dev);
        const double bytes_per_ns = 2.0 * mem_khz * 1e-6 * (bus_bits / 8) * (PACE * 1e-3);
        if (bytes_per_ns > 0) tile_ns_x16 = (uint32_t)(16.0 * NCTA * TILE_BYTES / bytes_per_ns);
        cudaFuncSetAttribute(decode_block_kernel, cudaFuncAttributeMaxDynamicSharedMemorySize, SMEM_BYTES);
    }
    Maps tm;
    make_map(enc, &tm.v, d_in[2], 64, (uint64_t)2 * NHEAD * SK * 2, 64, TILE_KEYS * 2, CU_TENSOR_MAP_SWIZZLE_128B);
    make_map(enc, &tm.wq, d_in[3], QCOLS, D_MODEL, 64, 128, CU_TENSOR_MAP_SWIZZLE_128B);
    make_map(enc, &tm.wo, d_in[4], D_MODEL, QCOLS, 64, 128, CU_TENSOR_MAP_SWIZZLE_128B);
    make_map(enc, &tm.w1, d_in[6], FF, D_MODEL, 32, 256, CU_TENSOR_MAP_SWIZZLE_64B);
    make_map(enc, &tm.w2, d_in[8], D_MODEL, FF, 64, 32, CU_TENSOR_MAP_SWIZZLE_128B, CU_TENSOR_MAP_L2_PROMOTION_L2_256B);
    decode_block_kernel<<<NCTA, NTHREADS, SMEM_BYTES>>>(
        tm, (const __nv_bfloat16*)d_in[0], (const __nv_bfloat16*)d_in[1], (const __nv_bfloat16*)d_in[7],
        (const __nv_bfloat16*)d_in[9], (__nv_bfloat16*)d_out, scr, tile_ns_x16);
}
```
